```python
import torch

def _softmax(x, axis=-1):
    return torch.softmax(x, dim=axis)
def _gelu(x):
    return torch.nn.functional.gelu(x, approximate="tanh")
def _silu(x):
    return torch.nn.functional.silu(x)
def _sigmoid(x):
    return torch.sigmoid(x)
def _layernorm(x, axis=-1, eps=1e-5):
    m = x.mean(dim=axis, keepdim=True)
    v = x.var(dim=axis, keepdim=True, unbiased=False)
    return (x - m) / torch.sqrt(v + eps)
def _scatter_add(tgt, idx, src, axis=0):
    return tgt.clone().index_add_(axis, idx, src)
def _segment_sum(src, seg, n):
    out = torch.zeros((n,) + src.shape[1:], dtype=src.dtype)
    return out.index_add_(0, seg, src)
def _pad(x, pw):
    flat = tuple(v for pair in reversed(pw) for v in pair)
    return torch.nn.functional.pad(x, flat)

kernel_name = 'interleave_layers__sliding_block_cached__mixer_channel_mlp__decode'

def setup_inputs():

    _w = (lambda a: (lambda t: t.to(torch.bfloat16) if t.is_floating_point() else t)(torch.as_tensor(a)))
    def _A_setup():
        B, Sq, D = 8, 1, 640
        Hq, Hkv, Sk, Dh = 32, 32, 4096, 128
        assert Hq % Hkv == 0, (Hq, Hkv)
        return {
            "x": _w((lambda *s: torch.randn(*s, dtype=torch.bfloat16) * 0.05)(B, Sq, D)),
            "k_cache": _w((lambda *s: torch.randn(*s, dtype=torch.bfloat16) * 3.2)(B, Hkv, Sk, Dh)),
            "v_cache": _w((lambda *s: torch.randn(*s, dtype=torch.bfloat16) * 0.4)(B, Hkv, Sk, Dh)),
            "wq": _w((lambda *s: torch.randn(*s, dtype=torch.bfloat16) * 3.2)(D, Hq * Dh) * (D ** -0.5)),
            "wo": _w((lambda *s: torch.randn(*s, dtype=torch.bfloat16) * 0.4)(Hq * Dh, D) * ((Hq * Dh) ** -0.5)),
        }
    _A_in = _A_setup()

    def _B_setup():
        B, S, D, F = 8, 1, 640, 1728
        return {
            "x": _w((lambda *s: torch.randn(*s, dtype=torch.bfloat16) * 0.05)(B, S, D)),
            "w1": _w((lambda *s: torch.randn(*s, dtype=torch.bfloat16) * 1.6)(D, F) * (D ** -0.5)),
            "b1": _w((lambda *s: torch.randn(*s, dtype=torch.bfloat16) * 1.6)(F)),
            "w2": _w((lambda *s: torch.randn(*s, dtype=torch.bfloat16) * 0.1)(F, D) * (F ** -0.5)),
            "b2": _w((lambda *s: torch.randn(*s, dtype=torch.bfloat16) * 0.1)(D)),
        }
    _B_in = _B_setup()

    return {
        "A_x": _A_in["x"],
        "A_k_cache": _A_in["k_cache"],
        "A_v_cache": _A_in["v_cache"],
        "A_wq": _A_in["wq"],
        "A_wo": _A_in["wo"],
        "B_x": _B_in["x"],
        "B_w1": _B_in["w1"],
        "B_b1": _B_in["b1"],
        "B_w2": _B_in["w2"],
        "B_b2": _B_in["b2"],
    }

def reference(A_x, A_k_cache, A_v_cache, A_wq, A_wo, B_x, B_w1, B_b1, B_w2, B_b2):
    def _A_ref(x, k_cache, v_cache, wq, wo):
        B, Sq, D = x.shape
        Hq, Dh = 32, 128
        Hkv, Sk = k_cache.shape[1], k_cache.shape[2]
        W = min(4096, max(256, Sk // 4))
        rep = Hq // Hkv
        q = (lambda x, *d: x.permute(*d))((x @ wq).reshape(B, Sq, Hq, Dh), 0, 2, 1, 3)
        k = (lambda x, n, axis: torch.repeat_interleave(x, n, dim=axis))(k_cache[:, :, Sk - W:, :], rep, axis=1)
        v = (lambda x, n, axis: torch.repeat_interleave(x, n, dim=axis))(v_cache[:, :, Sk - W:, :], rep, axis=1)
        scores = torch.einsum("bhqd,bhkd->bhqk", q, k) * (Dh ** -0.5)
        p = _softmax(scores, axis=-1)
        o = torch.einsum("bhqk,bhkd->bhqd", p, v)
        return (lambda x, *d: x.permute(*d))(o, 0, 2, 1, 3).reshape(B, Sq, Hq * Dh) @ wo

    def _B_ref(x, w1, b1, w2, b2):
        y = _layernorm(x, axis=-1)
        h = _gelu(torch.einsum("bsd,df->bsf", y, w1) + b1)
        return torch.einsum("bsf,fd->bsd", h, w2) + b2

    x = A_x
    x = x + _A_ref(_layernorm(x, axis=-1), A_k_cache, A_v_cache, A_wq, A_wo)
    x = x + _B_ref(_layernorm(x, axis=-1), B_w1, B_b1, B_w2, B_b2)
    x = x + _A_ref(_layernorm(x, axis=-1), A_k_cache, A_v_cache, A_wq, A_wo)
    x = x + _B_ref(_layernorm(x, axis=-1), B_w1, B_b1, B_w2, B_b2)
    return x
```

```cpp
#include <cuda_runtime.h>
#include <cuda.h>
#include <cuda_bf16.h>
#include <stdint.h>

namespace {

typedef unsigned long long u64;

constexpr int NB = 8, DM = 640, SK = 4096, WIN = 1024, FF = 1728;
constexpr int NCTA = 128, NGRP = 27;
constexpr int TILE = 16384;

constexpr int ST_WQ    = 65536;
constexpr int ST_W2    = ST_WQ + 40960;
constexpr int ST_WO    = 131072;
constexpr int ST_W1    = ST_WO + 40960;
constexpr int OFF_KX   = 196608;
constexpr int OFF_PART = OFF_KX + 16384;
constexpr int OFF_ML   = OFF_PART + 4 * 2048;
constexpr int OFF_O    = OFF_ML + 128;
constexpr int OFF_X1   = OFF_O + 3 * 256;
constexpr int OFF_H    = OFF_X1 + 3 * 320;
constexpr int OFF_X2   = OFF_H + 3 * 128;
constexpr int QSLOT    = 288;
constexpr int OFF_Q    = OFF_X2 + 2 * 320;
constexpr int OFF_P    = OFF_Q + 10 * QSLOT;
constexpr int OFF_CSQ  = OFF_P + 512;
constexpr int OFF_PREV = OFF_CSQ + 512;
constexpr int OFF_CS1  = OFF_PREV + 512;
constexpr int OFF_NEAR = OFF_CS1 + 256;
constexpr int OFF_BAR  = OFF_NEAR + 16;
constexpr int BAR_FULL = 0;
constexpr int BAR_W = 24;
constexpr int BAR_EMPTY = 36;
constexpr int BAR_Q2 = 48;
constexpr int BAR_Q1 = 50;
constexpr int BAR_WDONE = 62;
constexpr int BAR_DONE = 52;
constexpr int BAR_NEAR = 53;
constexpr int BAR_KR = 54;
constexpr int BAR_KFREE = 58;
constexpr int NBAR = 64;
constexpr int OFF_PROF = OFF_BAR + NBAR * 8;
constexpr int SMEM_BYTES = OFF_PROF;
constexpr int NB_QLAST = 0, NB_PART = 1, NB_O = 5, NB_X1 = 8, NB_H = 11, NB_X2 = 14;

constexpr unsigned CNT1 = 33, CNT2 = NGRP + 1;
constexpr float FIX_SCALE = 1073741824.0f;
constexpr float FIX_INV = 1.0f / 1073741824.0f;
constexpr int SPIN_LIMIT = 1 << 18;
constexpr int NFIRST = 4;

constexpr int DEPTH = 4;
constexpr int PACE = 340;
constexpr int BURST = 100000;
constexpr int PACE_OFF = 500, PACE_END = 16, DEPTH_END = 16, TAILGAP = 300, DEPTH0 = 5, XFLAGS = 0, RRLEAD = 5;
constexpr int DELAY_C = 0, DELAY_AR1 = 500, DELAY_U = 0, DELAY_AR2 = 450, DELAY_Q = 0;

constexpr int U_OFF = 32768, M_OFF = U_OFF + 2048, Q_OFF = 8192, QS_OFF = U_OFF + 2560, AR_OFF = 40960, FLAG_OFF = 524288 + 40960;
__host__ __device__ constexpr int boff(int slot) { return (slot & 1) * 128 + (slot >> 1) * 64; }
__host__ __device__ constexpr int voff(int v) { return (v & 1) * 16384 + ((v >> 1) & 1) * 262144 + (v >> 2) * 1048576; }
__device__ unsigned char g_xchg[4 << 20];

struct Params {
    CUtensorMap tq, to, t1, t2;
    const __nv_bfloat16 *x, *k, *v, *b1, *b2;
    __nv_bfloat16* out;
};

__device__ __forceinline__ unsigned clk() { unsigned c; asm volatile("mov.u32 %0, %%clock;" : "=r"(c)); return c; }
#define STAMP(idx) do {} while (0)

__device__ __forceinline__ void bail() { asm volatile("exit;"); }
__device__ __forceinline__ void mbar_init(uint32_t bar, uint32_t cnt) { asm volatile("mbarrier.init.shared::cta.b64 [%0], %1;" :: "r"(bar), "r"(cnt) : "memory"); }
__device__ __forceinline__ void mbar_expect_tx(uint32_t bar, uint32_t bytes) { asm volatile("mbarrier.arrive.expect_tx.shared::cta.b64 _, [%0], %1;" :: "r"(bar), "r"(bytes) : "memory"); }
__device__ __forceinline__ void mbar_arrive(uint32_t bar) { asm volatile("mbarrier.arrive.shared::cta.b64 _, [%0];" :: "r"(bar) : "memory"); }
__device__ __forceinline__ void mbar_wait(uint32_t bar, uint32_t parity) {
    int it = 0;
    while (true) {
        uint32_t ok;
        asm volatile("{\n.reg .pred p;\nmbarrier.try_wait.parity.shared::cta.b64 p, [%1], %2;\nselp.u32 %0, 1, 0, p;\n}" : "=r"(ok) : "r"(bar), "r"(parity) : "memory");
        if (ok) break;
        if (++it > SPIN_LIMIT) bail();
    }
}
__device__ __forceinline__ void mbar_wait_or_die(uint32_t bar, uint32_t parity) {
    int it = 0;
    while (true) {
        uint32_t ok;
        asm volatile("{\n.reg .pred p;\nmbarrier.try_wait.parity.shared::cta.b64 p, [%1], %2;\nselp.u32 %0, 1, 0, p;\n}" : "=r"(ok) : "r"(bar), "r"(parity) : "memory");
        if (ok) break;
        if (++it > SPIN_LIMIT) __trap();
    }
}
__device__ __forceinline__ void bulk_load(uint32_t dst, const void* src, uint32_t bytes, uint32_t bar, u64 pol) {
    asm volatile("cp.async.bulk.shared::cluster.global.mbarrier::complete_tx::bytes.L2::cache_hint [%0], [%1], %2, [%3], %4;"
                 :: "r"(dst), "l"(src), "r"(bytes), "r"(bar), "l"(pol) : "memory");
}
__device__ __forceinline__ void nb_sync(int id) { asm volatile("bar.sync %0, 160;" :: "r"(id) : "memory"); }
__device__ __forceinline__ void nb_arrive(int id) { asm volatile("bar.arrive %0, 160;" :: "r"(id) : "memory"); }
__device__ __forceinline__ void delay(unsigned n) { if (n) { unsigned c = clk(); while (clk() - c < n) {} } }

__device__ __forceinline__ uint4 lds128(uint32_t a) { uint4 v; asm volatile("ld.shared.v4.u32 {%0,%1,%2,%3}, [%4];" : "=r"(v.x), "=r"(v.y), "=r"(v.z), "=r"(v.w) : "r"(a)); return v; }
__device__ __forceinline__ uint2 lds64(uint32_t a) { uint2 v; asm volatile("ld.shared.v2.u32 {%0,%1}, [%2];" : "=r"(v.x), "=r"(v.y) : "r"(a)); return v; }
__device__ __forceinline__ float4 lds128f(uint32_t a) { float4 v; asm volatile("ld.shared.v4.f32 {%0,%1,%2,%3}, [%4];" : "=f"(v.x), "=f"(v.y), "=f"(v.z), "=f"(v.w) : "r"(a)); return v; }
__device__ __forceinline__ float2 lds64f(uint32_t a) { float2 v; asm volatile("ld.shared.v2.f32 {%0,%1}, [%2];" : "=f"(v.x), "=f"(v.y) : "r"(a)); return v; }
__device__ __forceinline__ unsigned lds32(uint32_t a) { unsigned v; asm volatile("ld.shared.u32 %0, [%1];" : "=r"(v) : "r"(a)); return v; }
__device__ __forceinline__ u64 lds64u(uint32_t a) { u64 v; asm volatile("ld.shared.u64 %0, [%1];" : "=l"(v) : "r"(a)); return v; }
__device__ __forceinline__ unsigned lds16(uint32_t a) { unsigned short v; asm volatile("ld.shared.u16 %0, [%1];" : "=h"(v) : "r"(a)); return v; }
__device__ __forceinline__ void sts128f(uint32_t a, float x, float y, float z, float w) { asm volatile("st.shared.v4.f32 [%0], {%1,%2,%3,%4};" :: "r"(a), "f"(x), "f"(y), "f"(z), "f"(w) : "memory"); }
__device__ __forceinline__ void sts64f(uint32_t a, float x, float y) { asm volatile("st.shared.v2.f32 [%0], {%1,%2};" :: "r"(a), "f"(x), "f"(y) : "memory"); }
__device__ __forceinline__ void sts64u(uint32_t a, u64 v) { asm volatile("st.shared.u64 [%0], %1;" :: "r"(a), "l"(v) : "memory"); }
__device__ __forceinline__ void sts32(uint32_t a, unsigned v) { asm volatile("st.shared.u32 [%0], %1;" :: "r"(a), "r"(v) : "memory"); }
__device__ __forceinline__ void sts16(uint32_t a, unsigned v) { asm volatile("st.shared.u16 [%0], %1;" :: "r"(a), "h"((unsigned short)v) : "memory"); }

__device__ __forceinline__ uint4 ld_rlx128(const void* p) { uint4 v; asm volatile("ld.relaxed.gpu.global.v4.u32 {%0,%1,%2,%3}, [%4];" : "=r"(v.x), "=r"(v.y), "=r"(v.z), "=r"(v.w) : "l"(p) : "memory"); return v; }
__device__ __forceinline__ void st_rlx128(void* p, uint4 v) { asm volatile("st.relaxed.gpu.global.v4.u32 [%0], {%1,%2,%3,%4};" :: "l"(p), "r"(v.x), "r"(v.y), "r"(v.z), "r"(v.w) : "memory"); }
__device__ __forceinline__ u64 ld_rlx64(const void* p) { u64 v; asm volatile("ld.relaxed.gpu.global.u64 %0, [%1];" : "=l"(v) : "l"(p) : "memory"); return v; }
__device__ __forceinline__ void red64(void* p, u64 v) { asm volatile("red.relaxed.gpu.global.add.u64 [%0], %1;" :: "l"(p), "l"(v) : "memory"); }

__device__ __forceinline__ uint4 ldg128_stream(const void* p, u64 pol) { uint4 v; asm volatile("ld.global.nc.L1::no_allocate.L2::cache_hint.v4.u32 {%0,%1,%2,%3}, [%4], %5;" : "=r"(v.x), "=r"(v.y), "=r"(v.z), "=r"(v.w) : "l"(p), "l"(pol)); return v; }
__device__ __forceinline__ uint2 ldg64(const void* p) { uint2 v; asm volatile("ld.global.nc.L1::no_allocate.v2.u32 {%0,%1}, [%2];" : "=r"(v.x), "=r"(v.y) : "l"(p)); return v; }
__device__ __forceinline__ unsigned ldg32(const void* p) { unsigned v; asm volatile("ld.global.nc.L1::no_allocate.u32 %0, [%1];" : "=r"(v) : "l"(p)); return v; }
__device__ __forceinline__ unsigned ldg16(const void* p) { unsigned short v; asm volatile("ld.global.nc.u16 %0, [%1];" : "=h"(v) : "l"(p)); return v; }

__device__ __forceinline__ void mma(float (&c)[4], unsigned a0, unsigned a1, unsigned a2, unsigned a3, unsigned b0, unsigned b1) {
    asm volatile("mma.sync.aligned.m16n8k16.row.col.f32.bf16.bf16.f32 {%0,%1,%2,%3}, {%4,%5,%6,%7}, {%8,%9}, {%0,%1,%2,%3};"
                 : "+f"(c[0]), "+f"(c[1]), "+f"(c[2]), "+f"(c[3]) : "r"(a0), "r"(a1), "r"(a2), "r"(a3), "r"(b0), "r"(b1));
}
__device__ __forceinline__ unsigned lolo(unsigned a, unsigned b) { return __byte_perm(a, b, 0x5410); }
__device__ __forceinline__ unsigned hihi(unsigned a, unsigned b) { return __byte_perm(a, b, 0x7632); }
__device__ __forceinline__ unsigned bf16_bits(float x) { return __bfloat16_as_ushort(__float2bfloat16_rn(x)); }
__device__ __forceinline__ float bf16_val(unsigned b) { return __uint_as_float(b << 16); }
__device__ __forceinline__ float bf16_round(float x) { return bf16_val(bf16_bits(x)); }
__device__ __forceinline__ unsigned pack_bf16(float lo, float hi) { unsigned r; asm("cvt.rn.bf16x2.f32 %0, %1, %2;" : "=r"(r) : "f"(hi), "f"(lo)); return r; }
__device__ __forceinline__ float ex2(float x) { float r; asm("ex2.approx.ftz.f32 %0, %1;" : "=f"(r) : "f"(x)); return r; }
__device__ __forceinline__ u64 to_fix(float v) { return ((u64)__float2ll_rn(v * FIX_SCALE) << 10) + 1ull; }
__device__ __forceinline__ float from_fix(u64 w) { return __ll2float_rn((long long)w >> 10) * FIX_INV; }
__device__ __forceinline__ uint2 ld_rlx64v(const void* p) { const u64 v = ld_rlx64(p); return make_uint2((unsigned)v, (unsigned)(v >> 32)); }
__device__ __forceinline__ void st_rlx64(void* p, unsigned x, unsigned y) { asm volatile("st.relaxed.gpu.global.u64 [%0], %1;" :: "l"(p), "l"((u64)x | ((u64)y << 32)) : "memory"); }
__device__ __forceinline__ unsigned char* xbase() { return (unsigned char*)(((size_t)g_xchg + 0x1fffff) & ~(size_t)0x1fffff); }

__device__ __forceinline__ uint32_t barq(uint32_t sb, int i) { return sb + OFF_BAR + i * 8; }
__device__ __forceinline__ float4 sum4(float4 a, float4 b, float4 c, float4 d) {
    return make_float4((a.x + b.x) + (c.x + d.x), (a.y + b.y) + (c.y + d.y), (a.z + b.z) + (c.z + d.z), (a.w + b.w) + (c.w + d.w));
}

__device__ __forceinline__ void item_of(int n, int& layer, int& b) {
    if (n == 0) { layer = 0; b = 0; }
    else if (n == 15) { layer = 1; b = 7; }
    else if (n & 1) { layer = 0; b = (n + 1) >> 1; }
    else { layer = 1; b = (n >> 1) - 1; }
}

constexpr size_t BSTRIDE = (size_t)32 * SK * 256;

__device__ __forceinline__ void tma2d(uint32_t dst, const CUtensorMap* tm, int c0, int c1, uint32_t bar) {
    u64 pol;
    asm("createpolicy.fractional.L2::evict_first.b64 %0, 1.0;" : "=l"(pol));
    asm volatile("cp.async.bulk.tensor.2d.shared::cluster.global.mbarrier::complete_tx::bytes.L2::cache_hint [%0], [%1, {%3, %4}], [%2], %5;"
                 :: "r"(dst), "l"(tm), "r"(bar), "r"(c0), "r"(c1), "l"(pol) : "memory");
}
constexpr int WP_WQ = 0, WP_W2 = 4, WP_W1 = 6, WP_WO = 8;
__device__ __forceinline__ void issue_weights(const Params& p, uint32_t sb, int m) {
    const int cta = blockIdx.x, h = cta >> 2, j = cta & 3;
    const uint32_t bar = barq(sb, BAR_W + m);
    if ((m & 12) == 4 && h >= NGRP) { mbar_arrive(bar); return; }
    mbar_expect_tx(bar, 10240);
    if (m < WP_W1) tma2d(sb + ST_W2 + (m - WP_W2) * 10240, &p.t2, 160 * j, 64 * h + 32 * (m - WP_W2), bar);
    else if (m < WP_WO) tma2d(sb + ST_W1 + (m - WP_W1) * 10240, &p.t1, 64 * h, 160 * j + 80 * (m - WP_W1), bar);
    else tma2d(sb + ST_WO + (m - WP_WO) * 10240, &p.to, 160 * j, 128 * h + 32 * (m - WP_WO), bar);
}
__device__ __forceinline__ unsigned gtime() { unsigned t; asm volatile("mov.u32 %0, %%globaltimer_lo;" : "=r"(t)); return t; }
#define PW 9
__device__ __forceinline__ bool elect_one() { unsigned r; asm volatile("{\n.reg .pred p;\nelect.sync _|p, 0xffffffff;\nselp.u32 %0, 1, 0, p;\n}" : "=r"(r)); return r; }
__device__ __forceinline__ void issue_reread(const Params& p, uint32_t sb, const char* kbase, int b, int w, int half, u64 pol) {
    if (XFLAGS & 2) { if (half == 0 && elect_one()) mbar_arrive(barq(sb, BAR_KR + w)); return; }
    const uint32_t bar = barq(sb, BAR_KR + w);
    const char* kp = kbase + b * BSTRIDE + w * TILE;
    if (elect_one()) {
        if (half == 0) { mbar_expect_tx(bar, TILE); bulk_load(sb + w * TILE, kp, 8192, bar, pol); }
        else { bulk_load(sb + w * TILE + 8192, kp + 8192, 4096, bar, pol); bulk_load(sb + OFF_KX + w * 4096, kp + 12288, 4096, bar, pol); }
    }
}
__device__ __forceinline__ void role_producer(const Params& p, uint32_t sb, const char* kbase, const char* vbase, unsigned t0) {
    u64 pol_first, pol_norm;
    asm volatile("createpolicy.fractional.L2::evict_first.b64 %0, 1.0;" : "=l"(pol_first));
    asm volatile("createpolicy.fractional.L2::evict_normal.b64 %0, 1.0;" : "=l"(pol_norm));
    STAMP(1);
#pragma unroll 1
    for (int m = 4; m < 12; m++) {
        if (m >= DEPTH0 - NFIRST) mbar_wait_or_die(barq(sb, m < DEPTH0 ? BAR_FULL + m + NFIRST - DEPTH0 : BAR_W + m - DEPTH0), 0);
        if (elect_one()) issue_weights(p, sb, m);
        STAMP(136 + 1 + 2 * m);
    }
    unsigned tnext = t0 + PACE_OFF + (15 + NFIRST - DEPTH) * PACE + (((blockIdx.x * 37) & 127) * PACE >> 7);
    uint32_t pbar = barq(sb, BAR_W + 12 - DEPTH), ppar = 0;
    int pleft = DEPTH, pgrp = -1;
#pragma unroll 1
    for (int grp = 0; grp < 2 * NB; grp++) {
        const int b = grp >> 1, isv = grp & 1, i0 = grp ? 0 : NFIRST;
        const int slot0 = isv ? 4 + (b & 1) * 4 : 0, use = isv ? b >> 1 : b;
        uint32_t bar = barq(sb, BAR_FULL + slot0 * 2 + i0), dst = sb + slot0 * TILE + i0 * (TILE / 2), ebar = barq(sb, BAR_EMPTY + slot0 + (i0 >> 1));
        const char* src = (isv ? vbase : kbase) + b * BSTRIDE + i0 * (TILE / 2);
        const u64 pol = (isv || (XFLAGS & 8)) && !(XFLAGS & 16) ? pol_first : pol_norm;
        if (grp == 1 || grp == 3) mbar_wait_or_die(barq(sb, BAR_WDONE + b), 0);
#pragma unroll 1
        for (int i = i0; i < 8; i++) {
            if (!(i & 1)) { if (!(isv && (XFLAGS & 1))) mbar_wait_or_die(ebar, (use & 1) ^ 1); ebar += 8; STAMP(136 + grp * 8 + i); }
            if (elect_one()) mbar_expect_tx(bar, TILE / 2);
            if (PACE > 0 && grp < PACE_END) { int it = 0; while ((int)(gtime() - tnext) < 0 && ++it < 4096) {} }
            if (grp < DEPTH_END) mbar_wait_or_die(pbar, ppar);
            if (elect_one()) bulk_load(dst, src, TILE / 2, bar, pol);
            if (PACE > 0) tnext += PACE + max((int)(gtime() - tnext) - BURST, 0);
            STAMP(grp * 8 + i);
            bar += 8; dst += TILE / 2; src += TILE / 2; pbar += 8;
            if (--pleft == 0) {
                pgrp++;
                pleft = pgrp ? 8 : 8 - NFIRST;
                const int pb = pgrp >> 1;
                pbar = barq(sb, BAR_FULL + ((pgrp & 1) ? 8 + (pb & 1) * 8 : pgrp ? 0 : NFIRST));
                ppar = ((pgrp & 1) ? pb >> 1 : pb) & 1;
            }
        }
    }
#pragma unroll 1
    for (int i = 0; i < 8; i++) {
        if (!(i & 1)) mbar_wait_or_die(barq(sb, BAR_KFREE + (i >> 1)), 0);
        issue_reread(p, sb, kbase, NB - 1, i >> 1, i & 1, pol_first);
        delay(TAILGAP);
    }
    mbar_wait_or_die(barq(sb, BAR_DONE), 0);
}

__device__ __forceinline__ uint4 pkt(float x, float y, float z, float w, unsigned tag) {
    return make_uint4(__float_as_uint(x), __float_as_uint(y), __float_as_uint(z), (__float_as_uint(w) & ~3u) | tag);
}
__device__ __forceinline__ float4 pksum(const uint4& a, const uint4& b, const uint4& c, const uint4& d) {
    return make_float4((__uint_as_float(a.x) + __uint_as_float(b.x)) + (__uint_as_float(c.x) + __uint_as_float(d.x)),
                       (__uint_as_float(a.y) + __uint_as_float(b.y)) + (__uint_as_float(c.y) + __uint_as_float(d.y)),
                       (__uint_as_float(a.z) + __uint_as_float(b.z)) + (__uint_as_float(c.z) + __uint_as_float(d.z)),
                       (__uint_as_float(a.w) + __uint_as_float(b.w)) + (__uint_as_float(c.w) + __uint_as_float(d.w)));
}
__device__ __forceinline__ float rsq(float x) { float r; asm("rsqrt.approx.ftz.f32 %0, %1;" : "=f"(r) : "f"(x)); return r; }
__device__ __forceinline__ float rcp(float x) { float r; asm("rcp.approx.ftz.f32 %0, %1;" : "=f"(r) : "f"(x)); return r; }
__device__ __forceinline__ void store_q(uint32_t sb, int qslot, int lane, float4 u, float4 cs, float mu, float rs) {
    const uint32_t qa = sb + OFF_Q + qslot * QSLOT + ((lane >> 1) & 3) * 32 + (lane >> 3) * 8 + (lane & 1) * 4;
    sts32(qa, pack_bf16((u.x - mu * cs.x) * rs, (u.y - mu * cs.y) * rs));
    sts32(qa + 144, pack_bf16((u.z - mu * cs.z) * rs, (u.w - mu * cs.w) * rs));
}

struct AttCtx {
    uint32_t sb;
    int w, lane, g, t;
    unsigned sel0, sel1;
};

__device__ __forceinline__ void softmax_part(const AttCtx& c, const float (&v)[8], float& m_out, float& l_out) {
    const bool ph = (c.t ^ c.g) & 1, hi = c.t >> 1;
    float u0 = ph ? v[1] : v[0], u1 = ph ? v[3] : v[2], u2 = ph ? v[5] : v[4], u3 = ph ? v[7] : v[6];
    const float sc = 0.08838834764831845f * 1.4426950408889634f;
    float s0 = (hi ? u2 : u0) * sc, s1 = (hi ? u3 : u1) * sc;
    float mx = fmaxf(s0, s1);
    int mi = __float_as_int(mx); mi ^= (mi >> 31) & 0x7fffffff;
    mi = __reduce_max_sync(0xffffffffu, mi);
    mi ^= (mi >> 31) & 0x7fffffff;
    const float m = __int_as_float(mi);
    const unsigned pp = pack_bf16(ex2(s0 - m), ex2(s1 - m));
    const uint32_t pa = c.sb + OFF_P + c.w * 128 + ((ph + 4 * hi) * 8 + c.g) * 2;
    sts16(pa, pp & 0xffffu);
    sts16(pa + 32, pp >> 16);
    float l = __uint_as_float(pp << 16) + __uint_as_float(pp & 0xffff0000u);
#pragma unroll
    for (int o = 16; o; o >>= 1) l += __shfl_xor_sync(0xffffffffu, l, o);
    m_out = m; l_out = l;
    __syncwarp();
}

__device__ __forceinline__ void load_q(const AttCtx& c, int qslot, uint2 (&qf)[4]) {
    const uint32_t qa = c.sb + OFF_Q + qslot * QSLOT + (c.g & 1) * 144 + c.t * 32;
    const int par = (c.g >> 1) & 1;
#pragma unroll
    for (int j = 0; j < 4; j++) qf[j] = lds64(qa + ((j ^ par) * 8));
}

template <int NT>
__device__ __forceinline__ void qk_tiles(const uint4 (*kr)[4], const uint2 (&qf)[4], float* v) {
    float acc[NT][4];
#pragma unroll
    for (int mt = 0; mt < NT; mt++) { acc[mt][0] = acc[mt][1] = acc[mt][2] = acc[mt][3] = 0.f; }
#pragma unroll
    for (int j = 0; j < 4; j++)
#pragma unroll
        for (int mt = 0; mt < NT; mt++) mma(acc[mt], kr[mt][j].x, kr[mt][j].y, kr[mt][j].z, kr[mt][j].w, qf[j].x, qf[j].y);
#pragma unroll
    for (int mt = 0; mt < NT; mt++) v[mt] = acc[mt][0] + acc[mt][3];
}
template <int NT>
__device__ __forceinline__ void k_from_smem(uint4 (*kr)[4], uint32_t aE, uint32_t aO) {
#pragma unroll
    for (int j = 0; j < 4; j++)
#pragma unroll
        for (int mt = 0; mt < NT; mt++) kr[mt][j] = lds128((((j ^ mt) & 1) ? aO : aE) + mt * 2048 + (j >> 1) * 128);
}

__device__ __forceinline__ void pv_half(const AttCtx& c, float (&o)[4][4], uint32_t va, uint32_t pa) {
#pragma unroll
    for (int i = 0; i < 4; i++) {
        const uint4 pw = lds128(pa + i * 16);
        const unsigned pv[4] = {pw.x, pw.y, pw.z, pw.w};
#pragma unroll
        for (int k = 0; k < 4; k++) {
            const uint2 a = lds64(va + (i * 8 + k * 2) * 256), b = lds64(va + (i * 8 + k * 2 + 1) * 256);
            mma(o[k], a.x, a.y, b.x, b.y, __byte_perm(pv[k], 0, c.sel0), __byte_perm(pv[k], 0, c.sel1));
        }
    }
}
__device__ __forceinline__ void publish_part(const AttCtx& c, const float (&o)[4][4], int slot, float m, float l) {
    sts128f(c.sb + OFF_PART + slot * 2048 + c.w * 512 + c.lane * 16,
            (o[0][0] + o[1][0]) + (o[2][0] + o[3][0]), (o[0][1] + o[1][1]) + (o[2][1] + o[3][1]),
            (o[0][2] + o[1][2]) + (o[2][2] + o[3][2]), (o[0][3] + o[1][3]) + (o[2][3] + o[3][3]));
    if (c.lane == 0) sts64f(c.sb + OFF_ML + slot * 32 + c.w * 8, m, l);
    nb_arrive(NB_PART + slot);
}

#undef PW
#define PW w
__device__ __forceinline__ void role_att(const Params& p, uint32_t sb, const char* kbase, int w) {
    u64 pol_first;
    asm volatile("createpolicy.fractional.L2::evict_first.b64 %0, 1.0;" : "=l"(pol_first));
    AttCtx c;
    c.sb = sb; c.w = w; c.lane = threadIdx.x & 31; c.g = c.lane >> 2; c.t = c.lane & 3;
    const bool act = (c.g >> 1) == c.t;
    c.sel0 = act ? ((c.g & 1) ? 0x1044u : 0x4410u) : 0x4444u;
    c.sel1 = act ? ((c.g & 1) ? 0x3244u : 0x4432u) : 0x4444u;
    const uint32_t offE = c.g * 256 + c.t * 16 + 64 * (c.g & 1);
    const uint32_t kE = sb + c.w * TILE + offE, kO = kE ^ 64;
    const uint32_t xE = sb + OFF_KX + c.w * 4096 + offE, xO = xE ^ 64;
    const uint32_t pa = sb + OFF_P + c.w * 128;
    const uint32_t barkr = barq(sb, BAR_KR + c.w);
    {
        const int lane = c.lane;
        float mu0, rs0;
        {
            float s1 = 0.f, s2 = 0.f;
#pragma unroll
            for (int u = 0; u < 5; u++) {
                const uint4 y = __ldg((const uint4*)(p.x + (2 * w + (lane >> 4)) * DM + 128 * u + 8 * (lane & 15)));
                const unsigned yy[4] = {y.x, y.y, y.z, y.w};
#pragma unroll
                for (int i = 0; i < 4; i++) {
                    const float x0 = __uint_as_float(yy[i] << 16), x1 = __uint_as_float(yy[i] & 0xffff0000u);
                    s1 += x0 + x1; s2 += fmaf(x0, x0, x1 * x1);
                }
            }
#pragma unroll
            for (int o = 8; o; o >>= 1) { s1 += __shfl_xor_sync(0xffffffffu, s1, o); s2 += __shfl_xor_sync(0xffffffffu, s2, o); }
            mu0 = s1 * (1.0f / DM);
            rs0 = rsq(fmaxf(s2 * (1.0f / DM) - mu0 * mu0, 0.f) + 1e-5f);
        }
        STAMP(128);
        mbar_wait(barq(sb, BAR_WDONE), 0);
        STAMP(129);
        const unsigned char* a = xbase() + (blockIdx.x >> 2) * 65536 + (lane >> 2) * 128 + (lane & 3) * 16;
        const unsigned char* a1 = a + (w & 1) * 16384 + (w >> 1) * 64;
        uint4 r[3][4];
        int it = 0;
        while (true) {
            unsigned d = 0;
#pragma unroll
            for (int i = 0; i < 4; i++) { r[0][i] = ld_rlx128(a + Q_OFF + i * 1024); r[1][i] = ld_rlx128(a1 + i * 1024); r[2][i] = ld_rlx128(a1 + 4096 + i * 1024); }
#pragma unroll
            for (int i = 0; i < 4; i++) d |= (r[0][i].w ^ 2u) | (r[1][i].w ^ 2u) | (r[2][i].w ^ 2u);
            if (__all_sync(0xffffffffu, (d & 3u) == 0)) break;
            if (++it > SPIN_LIMIT) bail();
        }
        const float4 cs = pksum(r[0][0], r[0][1], r[0][2], r[0][3]);
        if (w == 0) sts128f(sb + OFF_CSQ + lane * 16, cs.x, cs.y, cs.z, cs.w);
#pragma unroll
        for (int k = 0; k < 2; k++)
            store_q(sb, 2 * w + k, lane, pksum(r[1 + k][0], r[1 + k][1], r[1 + k][2], r[1 + k][3]), cs, __shfl_sync(0xffffffffu, mu0, k * 16), __shfl_sync(0xffffffffu, rs0, k * 16));
        __syncwarp();
        if (lane == 0) mbar_arrive(barq(sb, BAR_Q1));
        STAMP(130);
    }
    mbar_wait(barq(sb, BAR_Q1), 0);

#pragma unroll 1
    for (int b = 0; b <= NB; b++) {
        uint2 qf[4];
        float v[8], o[4][4], m, l;
        if (b < NB) {
            load_q(c, b, qf);
#pragma unroll
            for (int hh = 0; hh < 2; hh++) {
                uint4 kr[4][4];
                mbar_wait(barq(sb, BAR_FULL + c.w * 2 + hh), b & 1);
                k_from_smem<4>(kr, kE + hh * 8192, kO + hh * 8192);
                qk_tiles<4>(kr, qf, v + hh * 4);
            }
            STAMP(b * 16 + 0);
            softmax_part(c, v, m, l);
        }
        if (b == 0 || b == NB) { if (c.lane == 0) mbar_arrive(barq(sb, (b == 0 ? BAR_EMPTY : BAR_KFREE) + c.w)); }
        else {
#pragma unroll 1
            for (int hh = 0; hh < 2; hh++) {
                const int pos = 2 * c.w + hh - RRLEAD;
                if (pos >= 0) mbar_wait(barq(sb, BAR_FULL + 8 + (b & 1) * 8 + pos), (b >> 1) & 1);
                else mbar_wait(barq(sb, BAR_FULL + 8 + pos), b & 1);
                issue_reread(p, sb, kbase, b - 1, c.w, hh, pol_first);
            }
        }
        if (b < NB) {
            STAMP(b * 16 + 1);
            const int vs = 4 + (b & 1) * 4 + c.w;
#pragma unroll
            for (int i = 0; i < 4; i++) { o[i][0] = o[i][1] = o[i][2] = o[i][3] = 0.f; }
#pragma unroll
            for (int hh = 0; hh < 2; hh++) {
                mbar_wait(barq(sb, BAR_FULL + vs * 2 + hh), (b >> 1) & 1);
                if (hh) STAMP(b * 16 + 2);
                pv_half(c, o, sb + vs * TILE + hh * 8192 + c.lane * 8, pa + hh * 64);
            }
            publish_part(c, o, b & 1, m, l);
            STAMP(b * 16 + 3);
        }
        if (b > 0) {
            const int b2 = b - 1;
            uint4 kr[6][4];
            mbar_wait(barkr, b2 & 1);
            k_from_smem<6>(kr, kE, kO);
            asm volatile("" :: "r"(kr[5][3].x), "r"(kr[4][3].x), "r"(kr[3][3].x), "r"(kr[2][3].x), "r"(kr[1][3].x), "r"(kr[0][3].x) : "memory");
            __syncwarp();
            if (c.lane == 0) mbar_arrive(barq(sb, BAR_EMPTY + c.w));
            STAMP(b2 * 16 + 4);
            if (b == NB) { nb_sync(NB_QLAST); if (c.lane == 0) mbar_arrive(barq(sb, BAR_DONE)); }
            else mbar_wait(barq(sb, BAR_Q2 + (b2 & 1)), (b2 >> 1) & 1);
            STAMP(b2 * 16 + 5);
            load_q(c, 8 + (b2 & 1), qf);
            qk_tiles<4>(kr, qf, v);
            k_from_smem<2>(kr, xE, xO);
            qk_tiles<2>(kr + 4, qf, v + 4);
            qk_tiles<2>(kr, qf, v + 6);
            softmax_part(c, v, m, l);
            STAMP(b2 * 16 + 6);
            const int vs = 4 + (b2 & 1) * 4 + c.w;
#pragma unroll
            for (int i = 0; i < 4; i++) { o[i][0] = o[i][1] = o[i][2] = o[i][3] = 0.f; }
#pragma unroll
            for (int hh = 0; hh < 2; hh++) pv_half(c, o, sb + vs * TILE + hh * 8192 + c.lane * 8, pa + hh * 64);
            publish_part(c, o, 2 + (b2 & 1), m, l);
            if (c.lane == 0) mbar_arrive(barq(sb, BAR_EMPTY + vs));
            STAMP(b2 * 16 + 7);
        }
    }
}

__device__ __forceinline__ unsigned tagf(float x, unsigned tag) { return (__float_as_uint(x) & ~3u) | tag; }

__device__ __forceinline__ unsigned char* gptr(unsigned lo, unsigned hi) { u64 r; asm("mov.b64 %0, {%1, %2};" : "=l"(r) : "r"(lo), "r"(hi)); return (unsigned char*)r; }
__device__ __forceinline__ void poll4(const unsigned char* ra, const unsigned char* rm, unsigned tag, uint4& a0, uint4& a1, uint4& a2, uint4& a3,
                                      uint2& m0, uint2& m1, uint2& m2, uint2& m3) {
    int it = 0;
    while (true) {
        a0 = ld_rlx128(ra); a1 = ld_rlx128(ra + 1024); a2 = ld_rlx128(ra + 2048); a3 = ld_rlx128(ra + 3072);
        m0 = ld_rlx64v(rm); m1 = ld_rlx64v(rm + 128); m2 = ld_rlx64v(rm + 256); m3 = ld_rlx64v(rm + 384);
        if (__all_sync(0xffffffffu, ((((a0.w ^ tag) | (a1.w ^ tag) | (a2.w ^ tag)) | ((a3.w ^ tag) | (m0.y ^ tag) | (m1.y ^ tag)) | ((m2.y ^ tag) | (m3.y ^ tag))) & 3u) == 0)) break;
        if (++it > SPIN_LIMIT) bail();
    }
}

__device__ __forceinline__ void poll_x(const unsigned char* a, unsigned expect, u64 (&r)[5], uint32_t dst, float& s1, float& s2) {
    int it = 0;
    while (true) {
#pragma unroll
        for (int v = 0; v < 5; v++) r[v] = ld_rlx64(a + voff(v));
        unsigned d = 0;
#pragma unroll
        for (int v = 0; v < 5; v++) d |= (unsigned)r[v] ^ expect;
        if (__all_sync(0xffffffffu, (d & 1023u) == 0)) break;
        if (++it > SPIN_LIMIT) bail();
    }
    s1 = 0.f; s2 = 0.f;
#pragma unroll
    for (int v = 0; v < 5; v++) {
        const unsigned xbits = bf16_bits(from_fix(r[v]));
        sts16(dst + 64 * v, xbits);
        const float xv = bf16_val(xbits);
        s1 += xv; s2 = fmaf(xv, xv, s2);
    }
}

#undef PW
#define PW (6 + cw)
__device__ __forceinline__ void role_chain(const Params& p, uint32_t sb, int cw) {
    const int lane = threadIdx.x & 31, cta = blockIdx.x, h = cta >> 2, j = cta & 3;
    const int layer = cw >> 1;
    const bool mlp = h < NGRP;
    unsigned char* const S = xbase();
    unsigned char* const grp = S + h * 65536;
    const int cv = (lane & 7) < 5 ? (lane & 7) : 0;
    const bool cact = (lane & 7) < 5 && lane < 16;
    unsigned char* const cadr = S + AR_OFF + j * 65536 + (h >> 3) * 1024 + (h & 7) * 8 + voff(cv) + (lane >> 3) * 4096;
    const int ccol = 160 * j + 32 * cv + h;
    const float b2v = bf16_val(ldg16(p.b2 + ccol));
    unsigned resA = 0, resB = 0;
    if (!layer) {
        const __nv_bfloat16* xp = p.x + cw * DM + ccol;
        resA = ldg16(xp) | (ldg16(xp + 2 * DM) << 16); resB = ldg16(xp + 4 * DM) | (ldg16(xp + 6 * DM) << 16);
    }
    unsigned b1p = 0;
    if (mlp) b1p = ldg32(p.b1 + 64 * h + 2 * lane);
    if (cw == 1 && h < 20) {
        unsigned char* a = S + AR_OFF + j * 65536 + (h & 3) * 1024 + voff(h >> 2) + lane * 16;
        st_rlx128(a, make_uint4(0u, 0u, 0u, 0u)); st_rlx128(a + 4096, make_uint4(0u, 0u, 0u, 0u));
        asm volatile("fence.acq_rel.gpu;" ::: "memory");
        __syncwarp();
        if (lane < 2) st_rlx128(S + FLAG_OFF + j * 1024 + h * 32 + lane * 16, make_uint4(1u, 1u, 1u, 1u));
    }
    if (cw == 2) {
        const uint4 z = make_uint4(0u, 0u, 0u, 0u);
        unsigned char* const flag = S + FLAG_OFF + j * 1024;
        st_rlx128(grp + M_OFF + (lane >> 4) * 16384 + ((lane >> 3) & 1) * 4096 + j * 128 + (lane & 7) * 16, z);
        if (lane < 16) st_rlx128(grp + QS_OFF + (lane >> 3) * 4096 + j * 128 + (lane & 7) * 16, z);
        sts128f(sb + OFF_PREV + lane * 16, 0.f, 0.f, 0.f, 0.f);
        __syncwarp();
        mbar_wait(barq(sb, BAR_Q1), 0);
        unsigned best0 = ~0u, best1 = ~0u;
#pragma unroll 1
        for (int i = 0; i < 24; i++) {
            const unsigned t0 = clk();
            unsigned v, t1;
            asm volatile("{\n.reg .pred p;\nsetp.eq.u32 p, %2, 0;\nmov.u32 %0, 0;\n@p atom.relaxed.gpu.global.exch.b32 %0, [%1], 1;\n}"
                         : "=r"(v) : "l"(grp + QS_OFF + j * 128 + 64 + (i & 1) * 4096), "r"(lane) : "memory");
            asm volatile("and.b32 %0, %1, 0x80000000;" : "=r"(t1) : "r"(v) : "memory");
            t1 += clk();
            const unsigned dt = __shfl_sync(0xffffffffu, t1 - t0, 0);
            if (i & 1) best1 = min(best1, dt); else best0 = min(best0, dt);
            if (i >= 3 && min(best0, best1) < 390u && max(best0, best1) > min(best0, best1) + 90u) break;
        }
        const unsigned nb = best1 < best0;
        sts32(sb + OFF_NEAR, nb);
        STAMP(133);
        int it = 0;
        if (mlp) {
            mbar_wait(barq(sb, BAR_WDONE + 1), 0);
            const unsigned char* ru = grp + U_OFF + nb * 4096 + (lane >> 3) * 128 + (lane & 7) * 8;
            uint2 u0, u1, u2, u3;
            while (true) {
                u0 = ld_rlx64v(ru); u1 = ld_rlx64v(ru + 512); u2 = ld_rlx64v(ru + 1024); u3 = ld_rlx64v(ru + 1536);
                if (__all_sync(0xffffffffu, (((u0.y ^ 2u) | (u1.y ^ 2u) | (u2.y ^ 2u) | (u3.y ^ 2u)) & 3u) == 0)) break;
                if (++it > SPIN_LIMIT) bail();
            }
            sts64f(sb + OFF_CS1 + lane * 8, (__uint_as_float(u0.x) + __uint_as_float(u1.x)) + (__uint_as_float(u2.x) + __uint_as_float(u3.x)),
                   (__uint_as_float(u0.y) + __uint_as_float(u1.y)) + (__uint_as_float(u2.y) + __uint_as_float(u3.y)));
        }
        STAMP(134);
        if (lane < 8) st_rlx64(grp + M_OFF + j * 128 + (lane & 3) * 8 + (lane >> 2) * 4096, 0u, 2u);
        while (true) {
            unsigned f0;
            asm volatile("ld.acquire.gpu.global.u32 %0, [%1];" : "=r"(f0) : "l"(flag + (lane < 20 ? lane : 0) * 32) : "memory");
            const uint2 f1 = ld_rlx64v(grp + M_OFF + nb * 4096 + (lane & 3) * 128);
            if (__all_sync(0xffffffffu, f0 == 1u && (f1.y & 3u) != 0)) break;
            if (++it > SPIN_LIMIT) bail();
        }
        __syncwarp();
        if (lane == 0) mbar_arrive(barq(sb, BAR_NEAR));
    }
    mbar_wait(barq(sb, BAR_NEAR), 0);
    constexpr unsigned PMASK = (1u << 13) | (1u << 16) | (1u << 17) | (1u << 19);
    const unsigned nb = __shfl_sync(0xffffffffu, lds32(sb + OFF_NEAR), 0);
    const unsigned shi = (unsigned)((size_t)S >> 32), slo = (unsigned)(size_t)S;
    const unsigned ngr = nb << 12;
    const unsigned nar = ((nb ^ __popc(((AR_OFF + j * 65536) ^ (h * 65536)) & PMASK)) & 1) << 12;
    const unsigned l16 = (lane >> 2) * 128 + (lane & 3) * 16;
    const unsigned arn = slo + AR_OFF + j * 65536 + (lane >> 3) * 1024 + (lane & 7) * 8 + nar;
    const unsigned clo = (unsigned)(size_t)cadr;
    const uint32_t cx = (32 * cv + h) * 2;
    const unsigned sect = (lane & 3) * 8 + (lane >> 2) * 4096;
    STAMP(135);
#define GP(lo) gptr(lo, shi)
#define OPAQUE(x) asm volatile("" : "+r"(x))

#pragma unroll 1
    for (int b = layer ? 0 : cw; b < NB; b += 2 - layer) {
        int slot = layer * 2 + (b & 1);
        const int use = b >> 1;
        const unsigned tag = (use + 1) & 3, cbase = (use & 1) * 512;
        {
            unsigned res = (((use & 2) ? resB : resA) >> ((use & 1) * 16)) & 0xffffu;
            const unsigned gb = slo + h * 65536 + (slot & 1) * 16384;
            unsigned char* const wa = GP(gb + j * 1024 + layer * 64 + l16);
            unsigned char* const wm = GP(gb + M_OFF + j * 128 + layer * 32 + sect);
            const unsigned char* const ra = GP(gb + ngr + layer * 64 + l16);
            const unsigned char* const rm = GP(gb + ngr + M_OFF + layer * 32);
            const uint32_t pa = sb + OFF_PART + slot * 2048 + lane * 16;
            nb_sync(NB_PART + slot);
            STAMP(b * 16 + 0);
            const float4 ml0 = lds128f(sb + OFF_ML + slot * 32), ml1 = lds128f(sb + OFF_ML + slot * 32 + 16);
            const float4 p0 = lds128f(pa), p1 = lds128f(pa + 512), p2 = lds128f(pa + 1024), p3 = lds128f(pa + 1536);
            const float M = fmaxf(fmaxf(ml0.x, ml0.z), fmaxf(ml1.x, ml1.z));
            const float e0 = ex2(ml0.x - M), e1 = ex2(ml0.z - M), e2 = ex2(ml1.x - M), e3 = ex2(ml1.z - M);
            const uint4 pk = pkt((e0 * p0.x + e1 * p1.x) + (e2 * p2.x + e3 * p3.x), (e0 * p0.y + e1 * p1.y) + (e2 * p2.y + e3 * p3.y),
                                 (e0 * p0.z + e1 * p1.z) + (e2 * p2.z + e3 * p3.z), (e0 * p0.w + e1 * p1.w) + (e2 * p2.w + e3 * p3.w), tag);
            st_rlx128(wa, pk);
            st_rlx128(wa + 4096, pk);
            if (lane < 8) st_rlx64(wm, __float_as_uint(M), tagf((e0 * ml0.y + e1 * ml0.w) + (e2 * ml1.y + e3 * ml1.w), tag));
            if (cact) {
                if (layer) res = lds16(sb + OFF_X2 + (b & 1) * 320 + cx);
                red64(GP(clo + boff(slot)), to_fix(bf16_val(res)) + cbase - lds64u(sb + OFF_PREV + slot * 64 + cv * 8));
            }
            delay(DELAY_C);
            uint4 a0, a1, a2, a3;
            uint2 m0, m1, m2, m3;
            poll4(ra, rm, tag, a0, a1, a2, a3, m0, m1, m2, m3);
            STAMP(b * 16 + 1);
            const float M0 = __uint_as_float(m0.x), M1 = __uint_as_float(m1.x), M2 = __uint_as_float(m2.x), M3 = __uint_as_float(m3.x);
            const float Mg = fmaxf(fmaxf(M0, M1), fmaxf(M2, M3));
            const float f0 = ex2(M0 - Mg), f1 = ex2(M1 - Mg), f2 = ex2(M2 - Mg), f3 = ex2(M3 - Mg);
            const float inv = rcp((f0 * __uint_as_float(m0.y) + f1 * __uint_as_float(m1.y)) + (f2 * __uint_as_float(m2.y) + f3 * __uint_as_float(m3.y)));
            const float gx = (f0 * __uint_as_float(a0.x) + f1 * __uint_as_float(a1.x)) + (f2 * __uint_as_float(a2.x) + f3 * __uint_as_float(a3.x));
            const float gy = (f0 * __uint_as_float(a0.y) + f1 * __uint_as_float(a1.y)) + (f2 * __uint_as_float(a2.y) + f3 * __uint_as_float(a3.y));
            const float gz = (f0 * __uint_as_float(a0.z) + f1 * __uint_as_float(a1.z)) + (f2 * __uint_as_float(a2.z) + f3 * __uint_as_float(a3.z));
            const float gw = (f0 * __uint_as_float(a0.w) + f1 * __uint_as_float(a1.w)) + (f2 * __uint_as_float(a2.w) + f3 * __uint_as_float(a3.w));
            sts64u(sb + OFF_O + cw * 256 + lane * 8, (u64)pack_bf16(gx * inv, gy * inv) | ((u64)pack_bf16(gz * inv, gw * inv) << 32));
            nb_arrive(NB_O + cw);
        }
        STAMP(b * 16 + 2);
        OPAQUE(slot);
        {
            const unsigned char* const ra = GP(arn + boff(slot));
            unsigned char* const wm = GP(slo + h * 65536 + (slot & 1) * 16384 + M_OFF + j * 128 + 64 + layer * 32 + sect);
            delay(DELAY_AR1);
            u64 r[5];
            float s1, s2;
            poll_x(ra, cbase + CNT1, r, sb + OFF_X1 + cw * 320 + lane * 2, s1, s2);
            nb_arrive(NB_X1 + cw);
            STAMP(b * 16 + 3);
#pragma unroll
            for (int o = 16; o; o >>= 1) { s1 += __shfl_xor_sync(0xffffffffu, s1, o); s2 += __shfl_xor_sync(0xffffffffu, s2, o); }
            if (lane < 8 && mlp) st_rlx64(wm, __float_as_uint(s1), tagf(s2, tag));
            OPAQUE(slot);
            if (cact) red64(GP(clo + 256 + boff(slot)), to_fix(bf16_val(lds16(sb + OFF_X1 + cw * 320 + cx)) + b2v) + cbase - lds64u(sb + OFF_PREV + (4 + slot) * 64 + cv * 8));
            if (lane == h) {
#pragma unroll
                for (int v = 0; v < 5; v++) sts64u(sb + OFF_PREV + slot * 64 + v * 8, r[v]);
            }
        }
        if (mlp) {
            const unsigned ub = slo + h * 65536 + (slot & 1) * 16384 + ngr;
            const unsigned char* const ru = GP(ub + U_OFF + layer * 64 + (lane >> 3) * 128 + (lane & 7) * 8);
            const unsigned char* const rm = GP(ub + M_OFF + 64 + layer * 32);
            const float2 cs1 = lds64f(sb + OFF_CS1 + lane * 8);
            delay(DELAY_U);
            uint2 u0, u1, u2, u3, m0, m1, m2, m3;
            int it = 0;
            while (true) {
                u0 = ld_rlx64v(ru); u1 = ld_rlx64v(ru + 512); u2 = ld_rlx64v(ru + 1024); u3 = ld_rlx64v(ru + 1536);
                m0 = ld_rlx64v(rm); m1 = ld_rlx64v(rm + 128); m2 = ld_rlx64v(rm + 256); m3 = ld_rlx64v(rm + 384);
                if (__all_sync(0xffffffffu, ((((u0.y ^ tag) | (u1.y ^ tag) | (u2.y ^ tag)) | ((u3.y ^ tag) | (m0.y ^ tag) | (m1.y ^ tag)) | ((m2.y ^ tag) | (m3.y ^ tag))) & 3u) == 0)) break;
                if (++it > SPIN_LIMIT) bail();
            }
            STAMP(b * 16 + 4);
            const float mu = ((__uint_as_float(m0.x) + __uint_as_float(m1.x)) + (__uint_as_float(m2.x) + __uint_as_float(m3.x))) * (1.0f / DM);
            const float var = fmaxf(((__uint_as_float(m0.y) + __uint_as_float(m1.y)) + (__uint_as_float(m2.y) + __uint_as_float(m3.y))) * (1.0f / DM) - mu * mu, 0.f);
            const float rs = rsq(fmaf(var + 1e-5f, 1e-5f, var));
            const float x = (((__uint_as_float(u0.x) + __uint_as_float(u1.x)) + (__uint_as_float(u2.x) + __uint_as_float(u3.x))) - mu * cs1.x) * rs + __uint_as_float(b1p << 16);
            const float y = (((__uint_as_float(u0.y) + __uint_as_float(u1.y)) + (__uint_as_float(u2.y) + __uint_as_float(u3.y))) - mu * cs1.y) * rs + __uint_as_float(b1p & 0xffff0000u);
            constexpr float C0 = -2.0f * 0.7978845608028654f * 1.4426950408889634f;
            sts32(sb + OFF_H + cw * 128 + lane * 4, pack_bf16(x * rcp(1.0f + ex2(x * fmaf(x * x, 0.044715f * C0, C0))),
                                                             y * rcp(1.0f + ex2(y * fmaf(y * y, 0.044715f * C0, C0)))));
            nb_arrive(NB_H + cw);
        }
        STAMP(b * 16 + 5);
        OPAQUE(slot);
        if (layer) {
            if (b == NB - 1 && lane == 0) mbar_arrive(barq(sb, BAR_DONE));
            const unsigned char* const a = GP(clo - (lane >> 3) * 4096 + nar + 256 + boff(slot));
            const unsigned char* const a2 = h < 5 ? GP(arn + 256 + boff(slot) + voff(h)) : a;
            __nv_bfloat16* const o = p.out + 160 * j + 32 * h + lane;
            if (b == NB - 1 && h < 5) {
#pragma unroll
                for (int r = 0; r < NB - 1; r++) o[r * DM] = __ushort_as_bfloat16((unsigned short)lds16(sb + OFF_Q + r * QSLOT + lane * 2));
            }
            delay(mlp ? DELAY_AR2 : DELAY_AR2 + 600);
            u64 r, r2; int it = 0;
            while (true) {
                r2 = ld_rlx64(a2); r = ld_rlx64(a);
                if (__all_sync(0xffffffffu, ((((unsigned)r ^ (cbase + CNT2)) | ((unsigned)r2 ^ (cbase + CNT2))) & 1023u) == 0)) break;
                if (++it > SPIN_LIMIT) bail();
            }
            const unsigned ob = bf16_bits(from_fix(r2));
            if (b == NB - 1 && h < 5) o[(NB - 1) * DM] = __ushort_as_bfloat16((unsigned short)ob);
            sts16(sb + OFF_Q + b * QSLOT + lane * 2, ob);
            if (lane < 5) sts64u(sb + OFF_PREV + (4 + slot) * 64 + lane * 8, r);
            STAMP(b * 16 + 6);
        } else {
            const unsigned qb = slo + h * 65536;
            {
                const unsigned char* const ra = GP(arn + 256 + boff(slot));
                unsigned char* const wm = GP(qb + QS_OFF + j * 128 + cw * 32 + sect);
                delay(mlp ? DELAY_AR2 : DELAY_AR2 + 600);
                u64 r[5];
                float s1, s2;
                poll_x(ra, cbase + CNT2, r, sb + OFF_X2 + cw * 320 + lane * 2, s1, s2);
                nb_arrive(NB_X2 + cw);
                STAMP(b * 16 + 6);
#pragma unroll
                for (int o = 16; o; o >>= 1) { s1 += __shfl_xor_sync(0xffffffffu, s1, o); s2 += __shfl_xor_sync(0xffffffffu, s2, o); }
                if (lane < 8) st_rlx64(wm, __float_as_uint(s1), tagf(s2, tag));
                if (lane == h) {
#pragma unroll
                    for (int v = 0; v < 5; v++) sts64u(sb + OFF_PREV + (4 + slot) * 64 + v * 8, r[v]);
                }
            }
            const float4 cs = lds128f(sb + OFF_CSQ + lane * 16);
            delay(DELAY_Q);
            uint4 r0, r1, r2, r3;
            uint2 m0, m1, m2, m3;
            poll4(GP(qb + Q_OFF + (ngr ^ 4096) + cw * 64 + l16), GP(qb + QS_OFF + ngr + cw * 32), tag, r0, r1, r2, r3, m0, m1, m2, m3);
            STAMP(b * 16 + 7);
            const float mu = ((__uint_as_float(m0.x) + __uint_as_float(m1.x)) + (__uint_as_float(m2.x) + __uint_as_float(m3.x))) * (1.0f / DM);
            const float var = fmaxf(((__uint_as_float(m0.y) + __uint_as_float(m1.y)) + (__uint_as_float(m2.y) + __uint_as_float(m3.y))) * (1.0f / DM) - mu * mu, 0.f);
            store_q(sb, 8 + cw, lane, pksum(r0, r1, r2, r3), cs, mu, rsq(var + 1e-5f));
            if (b == NB - 1) nb_arrive(NB_QLAST);
            else { __syncwarp(); if (lane == 0) mbar_arrive(barq(sb, BAR_Q2 + cw)); }
            STAMP(b * 16 + 8);
        }
    }
    if (!layer) {
        if (cw == 1 && h < 20 && lane < 2) st_rlx128(S + FLAG_OFF + j * 1024 + h * 32 + lane * 16, make_uint4(0u, 0u, 0u, 0u));
        if (lane == 0) mbar_arrive(barq(sb, BAR_DONE));
    }
#undef GP
}

template <int NS>
__device__ __forceinline__ void load_wide(unsigned (&wf)[5][NS][4], uint32_t st, int w, int g, int t) {
    const uint32_t base = st + 8 * t * 320;
#pragma unroll
    for (int s = 0; s < NS; s++)
#pragma unroll
        for (int hf = 0; hf < 2; hf++)
#pragma unroll
            for (int e = 0; e < 2; e++) {
                const uint32_t r = base + (16 * NS * hf + 32 * (s >> 1) + 4 * (s & 1) + 2 * e) * 320;
                const uint2 r0 = lds64(r + 64 * w + 8 * g), r1 = lds64(r + 320 + 64 * w + 8 * g);
                const unsigned s0 = lds16(r + 256 + 16 * w + 2 * g), s1 = lds16(r + 320 + 256 + 16 * w + 2 * g);
                wf[0][s][hf + 2 * e] = lolo(r0.x, r1.x);
                wf[1][s][hf + 2 * e] = hihi(r0.x, r1.x);
                wf[2][s][hf + 2 * e] = lolo(r0.y, r1.y);
                wf[3][s][hf + 2 * e] = hihi(r0.y, r1.y);
                wf[4][s][hf + 2 * e] = lolo(s0, s1);
                asm volatile("" : "+r"(wf[4][s][hf + 2 * e]));
            }
}
template <int NS>
__device__ __forceinline__ void gemv_wide(const unsigned (&wf)[5][NS][4], uint32_t ba, unsigned lo0, unsigned lo1, unsigned hi, int t) {
    uint4 B[NS / 2];
#pragma unroll
    for (int u = 0; u < NS / 2; u++) B[u] = lds128(ba + 64 * u);
    float acc[5][4];
#pragma unroll
    for (int i = 0; i < 5; i++) { acc[i][0] = acc[i][1] = acc[i][2] = acc[i][3] = 0.f; }
#pragma unroll
    for (int s = 0; s < NS; s++)
#pragma unroll
        for (int i = 0; i < 5; i++)
            mma(acc[i], wf[i][s][0], wf[i][s][1], wf[i][s][2], wf[i][s][3], (s & 1) ? B[s >> 1].z : B[s >> 1].x, (s & 1) ? B[s >> 1].w : B[s >> 1].y);
    const float v0 = acc[0][0] + acc[0][3], v1 = acc[1][0] + acc[1][3], v2 = acc[2][0] + acc[2][3], v3 = acc[3][0] + acc[3][3];
    const u64 fa = to_fix((t & 2) ? ((t & 1) ? v3 : v2) : ((t & 1) ? v1 : v0)), fb = to_fix(acc[4][0] + acc[4][3]);
    unsigned char* const ra0 = gptr(lo0, hi);
    red64(ra0, fa);
    red64(ra0 + 4096, fa);
    if (t < 2) red64(gptr(lo1, hi), fb);
}

#undef PW
#define PW 4
__device__ __forceinline__ void role_g1(const Params& p, uint32_t sb, int w) {
    const int lane = threadIdx.x & 31, g = lane >> 2, t = lane & 3;
    const int cta = blockIdx.x, h = cta >> 2, j = cta & 3;
    const bool mlp = h < NGRP;
    unsigned wf[5][4][4], w1f[10][4];
    {
        mbar_wait(barq(sb, BAR_W + WP_W1), 0); mbar_wait(barq(sb, BAR_W + WP_W1 + 1), 0);
        const uint32_t base1 = sb + ST_W1 + 8 * t * 128 + 32 * w + 4 * g;
#pragma unroll
        for (int s = 0; s < 10; s++)
#pragma unroll
            for (int e = 0; e < 2; e++) {
                const uint32_t r = base1 + (32 * (s >> 1) + 4 * (s & 1) + 2 * e) * 128;
                const unsigned r0 = lds32(r), r1 = lds32(r + 128);
                w1f[s][2 * e] = lolo(r0, r1);
                w1f[s][2 * e + 1] = hihi(r0, r1);
            }
        float a[4] = {0.f, 0.f, 0.f, 0.f};
#pragma unroll
        for (int s = 0; s < 10; s++) mma(a, w1f[s][0], w1f[s][1], w1f[s][2], w1f[s][3], 0x3f803f80u, 0x3f803f80u);
        if (mlp) {
            unsigned char* ua = xbase() + h * 65536 + U_OFF + j * 512 + w * 128 + g * 8 + (t >> 1) * 64 + (t & 1) * 4096;
            st_rlx64(ua, __float_as_uint(a[0]), tagf(a[2], 2u));
            st_rlx64(ua + 16384, __float_as_uint(a[0]), tagf(a[2], 2u));
        }
#pragma unroll 1
        for (int m = WP_WO; m < WP_WO + 4; m++) mbar_wait(barq(sb, BAR_W + m), 0);
        load_wide<4>(wf, sb + ST_WO, w, g, t);
        __syncwarp();
        if (lane == 0) mbar_arrive(barq(sb, BAR_WDONE + 1));
    }
    STAMP(135);
    const unsigned shi = (unsigned)((size_t)xbase() >> 32), slo = (unsigned)(size_t)xbase();
    const unsigned ra0 = slo + AR_OFF + j * 65536 + (lane >> 3) * 1024 + (lane & 7) * 8 + voff(w);
    const unsigned gt = g * 8 + t * 4096;
    const unsigned ra1 = slo + AR_OFF + j * 65536 + w * 1024 + voff(4), ua = slo + h * 65536 + U_OFF + j * 512 + 128 * w;
    const uint32_t ob = sb + OFF_O + (g & 1) * 128 + t * 16, xb = sb + OFF_X1 + t * 16;
#pragma unroll 1
    for (int n = 0; n < 16; n++) {
        int layer, b; item_of(n, layer, b);
        const int slot = layer * 2 + (b & 1), cw = layer ? 2 : (b & 1);
        const unsigned tag = ((b >> 1) + 1) & 3;
        nb_sync(NB_O + cw);
        STAMP(n * 8 + 0);
        gemv_wide<4>(wf, ob + cw * 256, ra0 + boff(slot), gt + (ra1 + boff(slot)), shi, t);
        STAMP(n * 8 + 1);
        nb_sync(NB_X1 + cw);
        STAMP(n * 8 + 2);
        if (mlp) {
            uint4 B[5];
#pragma unroll
            for (int u = 0; u < 5; u++) B[u] = lds128(xb + cw * 320 + 64 * u);
            float a[4][4];
#pragma unroll
            for (int i = 0; i < 4; i++) { a[i][0] = a[i][1] = a[i][2] = a[i][3] = 0.f; }
#pragma unroll
            for (int s = 0; s < 10; s++)
                mma(a[s & 3], w1f[s][0], w1f[s][1], w1f[s][2], w1f[s][3], (s & 1) ? B[s >> 1].z : B[s >> 1].x, (s & 1) ? B[s >> 1].w : B[s >> 1].y);
            if (t < 2) st_rlx64(gptr(gt + (ua + (b & 1) * 16384 + layer * 64), shi), __float_as_uint((a[2][0] + a[3][0]) + (a[0][0] + a[1][0])), tagf((a[2][2] + a[3][2]) + (a[0][2] + a[1][2]), tag));
        }
        STAMP(n * 8 + 3);
    }
    if (lane == 0) mbar_arrive(barq(sb, BAR_DONE));
}

#undef PW
#define PW 5
__device__ __forceinline__ void role_g2(const Params& p, uint32_t sb, int w) {
    const int lane = threadIdx.x & 31, g = lane >> 2, t = lane & 3;
    const int cta = blockIdx.x, h = cta >> 2, j = cta & 3;
    const bool mlp = h < NGRP;
    unsigned wf[2][10][4], w2f[5][2][4];
    {
        uint4 X[5];
#pragma unroll
        for (int u = 0; u < 5; u++) X[u] = __ldg((const uint4*)(p.x + g * DM + 160 * j + 32 * u + 8 * t));
#pragma unroll 1
        for (int m = WP_WQ; m < WP_WQ + 4; m++) mbar_wait(barq(sb, BAR_W + m), 0);
        STAMP(130);
        const uint32_t base = sb + ST_WQ + 8 * t * 256 + 64 * w + 8 * g;
#pragma unroll
        for (int s = 0; s < 10; s++)
#pragma unroll
            for (int e = 0; e < 2; e++) {
                const uint32_t r = base + (32 * (s >> 1) + 4 * (s & 1) + 2 * e) * 256;
                const uint2 r0 = lds64(r), r1 = lds64(r + 256);
                wf[0][s][2 * e] = lolo(r0.x, r1.x);
                wf[0][s][2 * e + 1] = hihi(r0.x, r1.x);
                wf[1][s][2 * e] = lolo(r0.y, r1.y);
                wf[1][s][2 * e + 1] = hihi(r0.y, r1.y);
            }
        {
            float a[4] = {0.f, 0.f, 0.f, 0.f}, c[4] = {0.f, 0.f, 0.f, 0.f}, sa[4] = {0.f, 0.f, 0.f, 0.f}, sc[4] = {0.f, 0.f, 0.f, 0.f};
#pragma unroll
            for (int s = 0; s < 10; s++) {
                const unsigned b0 = (s & 1) ? X[s >> 1].z : X[s >> 1].x, b1 = (s & 1) ? X[s >> 1].w : X[s >> 1].y;
                mma(a, wf[0][s][0], wf[0][s][1], wf[0][s][2], wf[0][s][3], b0, b1);
                mma(c, wf[1][s][0], wf[1][s][1], wf[1][s][2], wf[1][s][3], b0, b1);
                mma(sa, wf[0][s][0], wf[0][s][1], wf[0][s][2], wf[0][s][3], 0x3f803f80u, 0x3f803f80u);
                mma(sc, wf[1][s][0], wf[1][s][1], wf[1][s][2], wf[1][s][3], 0x3f803f80u, 0x3f803f80u);
            }
            unsigned char* qm = xbase() + h * 65536 + j * 1024 + (2 * w + (g >> 2)) * 128 + (g & 3) * 16;
            st_rlx128(qm + (t & 1) * 16384 + (t >> 1) * 64, pkt(a[0], a[2], c[0], c[2], 2u));
            st_rlx128(qm + (t & 1) * 16384 + (t >> 1) * 64 + 4096, pkt(a[1], a[3], c[1], c[3], 2u));
            st_rlx128(qm + Q_OFF + (t >> 1) * 64 + (t & 1) * 4096, pkt(sa[0], sa[2], sc[0], sc[2], 2u));
        }
        mbar_wait(barq(sb, BAR_W + WP_W2), 0); mbar_wait(barq(sb, BAR_W + WP_W2 + 1), 0);
        load_wide<2>(w2f, sb + ST_W2, w, g, t);
        __syncwarp();
        if (lane == 0) mbar_arrive(barq(sb, BAR_WDONE));
        STAMP(131);
    }
    const unsigned shi = (unsigned)((size_t)xbase() >> 32), slo = (unsigned)(size_t)xbase();
    const unsigned ra0 = slo + AR_OFF + j * 65536 + (lane >> 3) * 1024 + (lane & 7) * 8 + voff(w) + 256;
    const unsigned ra1 = slo + AR_OFF + j * 65536 + w * 1024 + g * 8 + voff(4) + t * 4096 + 256;
    const unsigned qa = slo + h * 65536 + Q_OFF + j * 1024 + (2 * w + (g >> 2)) * 128 + (g & 3) * 16 + t * 4096;
    const uint32_t hb = sb + OFF_H + (g & 1) * 64 + t * 16, xb = sb + OFF_X2 + t * 16;
    STAMP(135);
#pragma unroll 1
    for (int n = 0; n < 16; n++) {
        int layer, b; item_of(n, layer, b);
        const int slot = layer * 2 + (b & 1), cw = layer ? 2 : (b & 1);
        if (mlp) {
            nb_sync(NB_H + cw);
            STAMP(n * 8 + 0);
            gemv_wide<2>(w2f, hb + cw * 128, ra0 + boff(slot), ra1 + boff(slot), shi, t);
            STAMP(n * 8 + 1);
        }
        if (layer == 0) {
            nb_sync(NB_X2 + cw);
            STAMP(n * 8 + 2);
            float a0[4] = {0.f, 0.f, 0.f, 0.f}, a1[4] = {0.f, 0.f, 0.f, 0.f}, c0[4] = {0.f, 0.f, 0.f, 0.f}, c1[4] = {0.f, 0.f, 0.f, 0.f};
            uint4 B[5];
#pragma unroll
            for (int u = 0; u < 5; u++) B[u] = lds128(xb + cw * 320 + 64 * u);
#pragma unroll
            for (int u = 0; u < 5; u++) {
                mma(a0, wf[0][2 * u][0], wf[0][2 * u][1], wf[0][2 * u][2], wf[0][2 * u][3], B[u].x, B[u].y);
                mma(c0, wf[1][2 * u][0], wf[1][2 * u][1], wf[1][2 * u][2], wf[1][2 * u][3], B[u].x, B[u].y);
                mma(a1, wf[0][2 * u + 1][0], wf[0][2 * u + 1][1], wf[0][2 * u + 1][2], wf[0][2 * u + 1][3], B[u].z, B[u].w);
                mma(c1, wf[1][2 * u + 1][0], wf[1][2 * u + 1][1], wf[1][2 * u + 1][2], wf[1][2 * u + 1][3], B[u].z, B[u].w);
            }
            if (t < 2) st_rlx128(gptr(qa + cw * 64, shi), pkt(a0[0] + a1[0], a0[2] + a1[2], c0[0] + c1[0], c0[2] + c1[2], ((b >> 1) + 1) & 3));
            STAMP(n * 8 + 3);
        }
    }
    if (lane == 0) mbar_arrive(barq(sb, BAR_DONE));
}

#define REG_ATT 128
#define REG_G1 152
#define REG_G2 160
#define REG_AUX 72
template <int N> __device__ __forceinline__ void set_regs() {
    if (N > 128) asm volatile("setmaxnreg.inc.sync.aligned.u32 %0;" :: "n"(N));
    if (N < 128) asm volatile("setmaxnreg.dec.sync.aligned.u32 %0;" :: "n"(N));
}

#define PROF_DUMP() do {} while (0)

__global__ void __launch_bounds__(512, 1) fused_kernel(const __grid_constant__ Params p) {
    extern __shared__ __align__(128) unsigned char smem[];
    const uint32_t sb = (uint32_t)__cvta_generic_to_shared(smem);
    const int cta = blockIdx.x;
    const unsigned t0 = gtime();
    const size_t kvoff = ((size_t)(cta >> 2) * SK + (SK - WIN) + (cta & 3) * 256) * 256;
    const char* kbase = (const char*)p.k + kvoff;
    const int warp = __shfl_sync(0xffffffffu, threadIdx.x >> 5, 0), lane = threadIdx.x & 31;
    if (warp < NFIRST) {
        if (elect_one()) {
            const uint32_t bar = barq(sb, BAR_FULL + warp);
            mbar_init(bar, 1);
            asm volatile("fence.mbarrier_init.release.cluster;" ::: "memory");
            mbar_expect_tx(bar, TILE / 2);
            asm volatile("cp.async.bulk.shared::cluster.global.mbarrier::complete_tx::bytes [%0], [%1], %2, [%3];"
                         :: "r"(sb + warp * (TILE / 2)), "l"(kbase + warp * (TILE / 2)), "r"(TILE / 2), "r"(bar) : "memory");
        }
#undef PW
#define PW 9
        STAMP(0);
    }
    asm volatile("" ::: "memory");
    if (warp >= 4 && warp < 8) {
        if (elect_one()) {
            const uint32_t bar = barq(sb, BAR_W + warp - 4);
            mbar_init(bar, 1);
            asm volatile("fence.mbarrier_init.release.cluster;" ::: "memory");
            mbar_expect_tx(bar, 10240);
            tma2d(sb + ST_WQ + (warp - 4) * 10240, &p.tq, (cta >> 2) * 128, 160 * (cta & 3) + 40 * (warp - 4), bar);
        }
    }
    asm volatile("" ::: "memory");
    if (warp >= 8) {
        if (elect_one()) {
#pragma unroll 1
            for (int bi = warp - 4; bi < NBAR; bi += 8)
                if ((bi & ~3) != BAR_W) mbar_init(barq(sb, bi), (bi == BAR_Q1 || bi >= BAR_WDONE) ? 4 : bi == BAR_DONE ? 15 : 1);
            asm volatile("fence.mbarrier_init.release.cluster;" ::: "memory");
            if (warp >= 13) asm volatile("prefetch.tensormap [%0];" :: "l"(&p.tq + (warp - 12)) : "memory");
        }
    }
    __syncthreads();
    if (warp < 4) {
        set_regs<REG_ATT>();
        role_att(p, sb, kbase, warp);
        PROF_DUMP();
    } else if (warp < 8) {
        set_regs<REG_G1>();
        role_g1(p, sb, warp - 4);
        PROF_DUMP();
    } else if (warp < 12) {
        set_regs<REG_G2>();
        role_g2(p, sb, warp - 8);
        PROF_DUMP();
    } else {
        set_regs<REG_AUX>();
        if (warp == 12) role_producer(p, sb, kbase, (const char*)p.v + kvoff, t0);
        else role_chain(p, sb, warp - 13);
        PROF_DUMP();
    }
}

}

typedef CUresult (*EncodeTiledFn)(CUtensorMap*, CUtensorMapDataType, cuuint32_t, void*, const cuuint64_t*, const cuuint64_t*, const cuuint32_t*,
                                  const cuuint32_t*, CUtensorMapInterleave, CUtensorMapSwizzle, CUtensorMapL2promotion, CUtensorMapFloatOOBfill);

static void make_map(EncodeTiledFn enc, CUtensorMap* tm, void* ptr, int cols, int rows, int bcols, int brows) {
    cuuint64_t gd[2] = {(cuuint64_t)cols, (cuuint64_t)rows}, gs[1] = {(cuuint64_t)cols * 2};
    cuuint32_t bd[2] = {(cuuint32_t)bcols, (cuuint32_t)brows}, es[2] = {1, 1};
    enc(tm, CU_TENSOR_MAP_DATA_TYPE_BFLOAT16, 2, ptr, gd, gs, bd, es, CU_TENSOR_MAP_INTERLEAVE_NONE, CU_TENSOR_MAP_SWIZZLE_NONE,
        CU_TENSOR_MAP_L2_PROMOTION_NONE, CU_TENSOR_MAP_FLOAT_OOB_FILL_NONE);
}

extern "C" void kernel_launch(void* const* d_in, const int* in_sizes, int n_in, void* d_out, int out_size) {
    void* fn = nullptr;
    cudaDriverEntryPointQueryResult qr;
    cudaGetDriverEntryPoint("cuTensorMapEncodeTiled", &fn, cudaEnableDefault, &qr);
    Params p;
    make_map((EncodeTiledFn)fn, &p.tq, d_in[3], 4096, DM, 128, 40);
    make_map((EncodeTiledFn)fn, &p.to, d_in[4], DM, 4096, 160, 32);
    make_map((EncodeTiledFn)fn, &p.t1, d_in[6], FF, DM, 64, 80);
    make_map((EncodeTiledFn)fn, &p.t2, d_in[8], DM, FF, 160, 32);
    p.x = (const __nv_bfloat16*)d_in[0];
    p.k = (const __nv_bfloat16*)d_in[1];
    p.v = (const __nv_bfloat16*)d_in[2];
    p.b1 = (const __nv_bfloat16*)d_in[7];
    p.b2 = (const __nv_bfloat16*)d_in[9];
    p.out = (__nv_bfloat16*)d_out;
    cudaFuncSetAttribute(fused_kernel, cudaFuncAttributeMaxDynamicSharedMemorySize, SMEM_BYTES);
    fused_kernel<<<NCTA, 512, SMEM_BYTES>>>(p);
}
```

```cpp
#include <cuda_runtime.h>
#include <cuda.h>
#include <cuda_bf16.h>
#include <stdint.h>

namespace {

typedef unsigned long long u64;

constexpr int NB = 8, DM = 640, SK = 4096, WIN = 1024, FF = 1728;
constexpr int NCTA = 128, NGRP = 27;
constexpr int TILE = 16384;

constexpr int ST_WQ    = 65536;
constexpr int ST_W2    = ST_WQ + 40960;
constexpr int ST_WO    = 131072;
constexpr int ST_W1    = ST_WO + 40960;
constexpr int OFF_KX   = 196608;
__host__ __device__ constexpr int kx_off(int par) { return par ? OFF_KX : 49152; }
constexpr int OFF_PART = OFF_KX + 16384;
constexpr int OFF_ML   = OFF_PART + 4 * 2048;
constexpr int OFF_O    = OFF_ML + 128;
constexpr int OFF_X1   = OFF_O + 3 * 256;
constexpr int OFF_H    = OFF_X1 + 3 * 320;
constexpr int OFF_X2   = OFF_H + 3 * 128;
constexpr int QSLOT    = 288;
constexpr int OFF_Q    = OFF_X2 + 2 * 320;
constexpr int OFF_P    = OFF_Q + 10 * QSLOT;
constexpr int OFF_CSQ  = OFF_P + 512;
constexpr int OFF_PREV = OFF_CSQ + 512;
constexpr int OFF_CS1  = OFF_PREV + 512;
constexpr int OFF_NEAR = OFF_CS1 + 256;
constexpr int OFF_BAR  = OFF_NEAR + 32;
constexpr int BAR_FULL = 0;
constexpr int BAR_W = 24;
constexpr int BAR_EMPTY = 36;
constexpr int BAR_Q2 = 48;
constexpr int BAR_Q1 = 50;
constexpr int BAR_WDONE = 62;
constexpr int BAR_L25 = 51;
constexpr int BAR_DONE = 52;
constexpr int BAR_NEAR = 53;
constexpr int BAR_KR = 54;
constexpr int BAR_KXE = 58;
constexpr int BAR_ML = 64;
constexpr int NBAR = 68;
constexpr int OFF_PROF = OFF_BAR + NBAR * 8;
constexpr int SMEM_BYTES = OFF_PROF;
constexpr int NB_QLAST = 0, NB_PART = 1, NB_O = 5, NB_X1 = 8, NB_H = 11, NB_X2 = 14;

constexpr unsigned CNT1 = 33, CNT2 = NGRP + 1;
constexpr float FIX_SCALE = 1099511627776.0f;
constexpr int SPIN_LIMIT = 1 << 18;
constexpr int NFIRST = 4;

constexpr int DEPTH = 4;
constexpr int PACE = 327;
constexpr int PACE_OFF = 0, START_T = 2900, PACE_W1 = 345, PACE_W = 410, TAILGAP = 100, XFLAGS = 0, RRLEAD = 2;
constexpr int DELAY_AR1 = 500, DELAY_U = 0, DELAY_AR2 = 450, DELAY_Q = 0;

constexpr int U_OFF = 32768, M_OFF = U_OFF + 2048, Q_OFF = 8192, QS_OFF = U_OFF + 2560, AR_OFF = 40960, FLAG_OFF = 524288 + 40960;
__host__ __device__ constexpr int boff(int slot) { return (slot & 1) * 128 + (slot >> 1) * 64; }
__host__ __device__ constexpr int voff(int v) { return (v & 1) * 16384 + ((v >> 1) & 1) * 262144 + (v >> 2) * 1048576; }
__device__ unsigned char g_xchg[4 << 20];

struct Params {
    CUtensorMap tq, to, t1, t2;
    const __nv_bfloat16 *x, *k, *v, *b1, *b2;
    __nv_bfloat16* out;
    float zero;
};

__device__ __forceinline__ unsigned clk() { unsigned c; asm volatile("mov.u32 %0, %%clock;" : "=r"(c)); return c; }
#define STAMP(idx) do {} while (0)

__device__ __forceinline__ void bail() { asm volatile("exit;"); }
__device__ __forceinline__ void mbar_init(uint32_t bar, uint32_t cnt) { asm volatile("mbarrier.init.shared::cta.b64 [%0], %1;" :: "r"(bar), "r"(cnt) : "memory"); }
__device__ __forceinline__ void mbar_expect_tx(uint32_t bar, uint32_t bytes) { asm volatile("mbarrier.arrive.expect_tx.shared::cta.b64 _, [%0], %1;" :: "r"(bar), "r"(bytes) : "memory"); }
__device__ __forceinline__ void mbar_arrive(uint32_t bar) { asm volatile("mbarrier.arrive.shared::cta.b64 _, [%0];" :: "r"(bar) : "memory"); }
__device__ __forceinline__ void mbar_wait(uint32_t bar, uint32_t parity) {
    int it = 0;
    while (true) {
        uint32_t ok;
        asm volatile("{\n.reg .pred p;\nmbarrier.try_wait.parity.shared::cta.b64 p, [%1], %2;\nselp.u32 %0, 1, 0, p;\n}" : "=r"(ok) : "r"(bar), "r"(parity) : "memory");
        if (ok) break;
        if (++it > SPIN_LIMIT) bail();
    }
}
__device__ __forceinline__ void mbar_wait_or_die(uint32_t bar, uint32_t parity) {
    int it = 0;
    while (true) {
        uint32_t ok;
        asm volatile("{\n.reg .pred p;\nmbarrier.try_wait.parity.shared::cta.b64 p, [%1], %2;\nselp.u32 %0, 1, 0, p;\n}" : "=r"(ok) : "r"(bar), "r"(parity) : "memory");
        if (ok) break;
        if (++it > SPIN_LIMIT) __trap();
    }
}
__device__ __forceinline__ void bulk_load(uint32_t dst, const void* src, uint32_t bytes, uint32_t bar, u64 pol) {
    asm volatile("cp.async.bulk.shared::cluster.global.mbarrier::complete_tx::bytes.L2::cache_hint [%0], [%1], %2, [%3], %4;"
                 :: "r"(dst), "l"(src), "r"(bytes), "r"(bar), "l"(pol) : "memory");
}
__device__ __forceinline__ void nb_sync(int id) { asm volatile("bar.sync %0, 160;" :: "r"(id) : "memory"); }
__device__ __forceinline__ void nb_arrive(int id) { asm volatile("bar.arrive %0, 160;" :: "r"(id) : "memory"); }
__device__ __forceinline__ void delay(unsigned n) { if (n) { unsigned c = clk(); while (clk() - c < n) {} } }

__device__ __forceinline__ uint4 lds128(uint32_t a) { uint4 v; asm volatile("ld.shared.v4.u32 {%0,%1,%2,%3}, [%4];" : "=r"(v.x), "=r"(v.y), "=r"(v.z), "=r"(v.w) : "r"(a)); return v; }
__device__ __forceinline__ uint2 lds64(uint32_t a) { uint2 v; asm volatile("ld.shared.v2.u32 {%0,%1}, [%2];" : "=r"(v.x), "=r"(v.y) : "r"(a)); return v; }
__device__ __forceinline__ float4 lds128f(uint32_t a) { float4 v; asm volatile("ld.shared.v4.f32 {%0,%1,%2,%3}, [%4];" : "=f"(v.x), "=f"(v.y), "=f"(v.z), "=f"(v.w) : "r"(a)); return v; }
__device__ __forceinline__ float2 lds64f(uint32_t a) { float2 v; asm volatile("ld.shared.v2.f32 {%0,%1}, [%2];" : "=f"(v.x), "=f"(v.y) : "r"(a)); return v; }
__device__ __forceinline__ unsigned lds32(uint32_t a) { unsigned v; asm volatile("ld.shared.u32 %0, [%1];" : "=r"(v) : "r"(a)); return v; }
__device__ __forceinline__ u64 lds64u(uint32_t a) { u64 v; asm volatile("ld.shared.u64 %0, [%1];" : "=l"(v) : "r"(a)); return v; }
__device__ __forceinline__ unsigned lds16(uint32_t a) { unsigned short v; asm volatile("ld.shared.u16 %0, [%1];" : "=h"(v) : "r"(a)); return v; }
__device__ __forceinline__ void sts128f(uint32_t a, float x, float y, float z, float w) { asm volatile("st.shared.v4.f32 [%0], {%1,%2,%3,%4};" :: "r"(a), "f"(x), "f"(y), "f"(z), "f"(w) : "memory"); }
__device__ __forceinline__ void sts64f(uint32_t a, float x, float y) { asm volatile("st.shared.v2.f32 [%0], {%1,%2};" :: "r"(a), "f"(x), "f"(y) : "memory"); }
__device__ __forceinline__ void sts64u(uint32_t a, u64 v) { asm volatile("st.shared.u64 [%0], %1;" :: "r"(a), "l"(v) : "memory"); }
__device__ __forceinline__ void sts32(uint32_t a, unsigned v) { asm volatile("st.shared.u32 [%0], %1;" :: "r"(a), "r"(v) : "memory"); }
__device__ __forceinline__ void sts16(uint32_t a, unsigned v) { asm volatile("st.shared.u16 [%0], %1;" :: "r"(a), "h"((unsigned short)v) : "memory"); }

__device__ __forceinline__ uint4 ld_rlx128(const void* p) { uint4 v; asm volatile("ld.relaxed.gpu.global.v4.u32 {%0,%1,%2,%3}, [%4];" : "=r"(v.x), "=r"(v.y), "=r"(v.z), "=r"(v.w) : "l"(p) : "memory"); return v; }
__device__ __forceinline__ void st_rlx128(void* p, uint4 v) { asm volatile("st.relaxed.gpu.global.v4.u32 [%0], {%1,%2,%3,%4};" :: "l"(p), "r"(v.x), "r"(v.y), "r"(v.z), "r"(v.w) : "memory"); }
__device__ __forceinline__ u64 ld_rlx64(const void* p) { u64 v; asm volatile("ld.relaxed.gpu.global.u64 %0, [%1];" : "=l"(v) : "l"(p) : "memory"); return v; }
__device__ __forceinline__ void red64(void* p, u64 v) { asm volatile("red.relaxed.gpu.global.add.u64 [%0], %1;" :: "l"(p), "l"(v) : "memory"); }

__device__ __forceinline__ uint4 ldg128_stream(const void* p, u64 pol) { uint4 v; asm volatile("ld.global.nc.L1::no_allocate.L2::cache_hint.v4.u32 {%0,%1,%2,%3}, [%4], %5;" : "=r"(v.x), "=r"(v.y), "=r"(v.z), "=r"(v.w) : "l"(p), "l"(pol)); return v; }
__device__ __forceinline__ uint2 ldg64(const void* p) { uint2 v; asm volatile("ld.global.nc.L1::no_allocate.v2.u32 {%0,%1}, [%2];" : "=r"(v.x), "=r"(v.y) : "l"(p)); return v; }
__device__ __forceinline__ unsigned ldg32(const void* p) { unsigned v; asm volatile("ld.global.nc.L1::no_allocate.u32 %0, [%1];" : "=r"(v) : "l"(p)); return v; }
__device__ __forceinline__ unsigned ldg16(const void* p) { unsigned short v; asm volatile("ld.global.nc.u16 %0, [%1];" : "=h"(v) : "l"(p)); return v; }

__device__ __forceinline__ void mma(float (&c)[4], unsigned a0, unsigned a1, unsigned a2, unsigned a3, unsigned b0, unsigned b1) {
    asm volatile("mma.sync.aligned.m16n8k16.row.col.f32.bf16.bf16.f32 {%0,%1,%2,%3}, {%4,%5,%6,%7}, {%8,%9}, {%0,%1,%2,%3};"
                 : "+f"(c[0]), "+f"(c[1]), "+f"(c[2]), "+f"(c[3]) : "r"(a0), "r"(a1), "r"(a2), "r"(a3), "r"(b0), "r"(b1));
}
__device__ __forceinline__ unsigned lolo(unsigned a, unsigned b) { return __byte_perm(a, b, 0x5410); }
__device__ __forceinline__ unsigned hihi(unsigned a, unsigned b) { return __byte_perm(a, b, 0x7632); }
__device__ __forceinline__ unsigned bf16_bits(float x) { return __bfloat16_as_ushort(__float2bfloat16_rn(x)); }
__device__ __forceinline__ float bf16_val(unsigned b) { return __uint_as_float(b << 16); }
__device__ __forceinline__ float bf16_round(float x) { return bf16_val(bf16_bits(x)); }
__device__ __forceinline__ unsigned pack_bf16(float lo, float hi) { unsigned r; asm("cvt.rn.bf16x2.f32 %0, %1, %2;" : "=r"(r) : "f"(hi), "f"(lo)); return r; }
__device__ __forceinline__ float ex2(float x) { float r; asm("ex2.approx.ftz.f32 %0, %1;" : "=f"(r) : "f"(x)); return r; }
__device__ __forceinline__ u64 to_fix_scaled(float vs) { return ((u64)__float2ll_rn(vs) & ~1023ull) | 1ull; }
__device__ __forceinline__ u64 to_fix(float v) { return to_fix_scaled(v * FIX_SCALE); }
__device__ __forceinline__ float from_fix(u64 w) {
    return fmaf(__uint2float_rn((unsigned)w & ~1023u), 1.0f / FIX_SCALE, __int2float_rn((int)(w >> 32)) * (1.0f / 256.0f));
}
__device__ __forceinline__ uint2 ld_rlx64v(const void* p) { const u64 v = ld_rlx64(p); return make_uint2((unsigned)v, (unsigned)(v >> 32)); }
__device__ __forceinline__ void st_rlx64(void* p, unsigned x, unsigned y) { asm volatile("st.relaxed.gpu.global.u64 [%0], %1;" :: "l"(p), "l"((u64)x | ((u64)y << 32)) : "memory"); }
__device__ __forceinline__ void st_rlx64_if(bool c, void* p, unsigned x, unsigned y) {
    asm volatile("{\n.reg .pred p;\nsetp.ne.u32 p, %3, 0;\n@p st.relaxed.gpu.global.v2.u32 [%0], {%1, %2};\n}" :: "l"(p), "r"(x), "r"(y), "r"((unsigned)c) : "memory");
}
__device__ __forceinline__ void st_rlx128_if(bool c, void* p, uint4 v) {
    asm volatile("{\n.reg .pred p;\nsetp.ne.u32 p, %5, 0;\n@p st.relaxed.gpu.global.v4.u32 [%0], {%1, %2, %3, %4};\n}"
                 :: "l"(p), "r"(v.x), "r"(v.y), "r"(v.z), "r"(v.w), "r"((unsigned)c) : "memory");
}
__device__ __forceinline__ unsigned char* xbase() { return (unsigned char*)(((size_t)g_xchg + 0x1fffff) & ~(size_t)0x1fffff); }

__device__ __forceinline__ uint32_t barq(uint32_t sb, int i) { return sb + OFF_BAR + i * 8; }
__device__ __forceinline__ float4 sum4(float4 a, float4 b, float4 c, float4 d) {
    return make_float4((a.x + b.x) + (c.x + d.x), (a.y + b.y) + (c.y + d.y), (a.z + b.z) + (c.z + d.z), (a.w + b.w) + (c.w + d.w));
}

__device__ __forceinline__ void item_of(int n, int& layer, int& b) {
    if (n == 0) { layer = 0; b = 0; }
    else if (n == 15) { layer = 1; b = 7; }
    else if (n & 1) { layer = 0; b = (n + 1) >> 1; }
    else { layer = 1; b = (n >> 1) - 1; }
}

constexpr size_t BSTRIDE = (size_t)32 * SK * 256;

__device__ __forceinline__ void tma2d(uint32_t dst, const CUtensorMap* tm, int c0, int c1, uint32_t bar) {
    u64 pol;
    asm("createpolicy.fractional.L2::evict_first.b64 %0, 1.0;" : "=l"(pol));
    asm volatile("cp.async.bulk.tensor.2d.shared::cluster.global.mbarrier::complete_tx::bytes.L2::cache_hint [%0], [%1, {%3, %4}], [%2], %5;"
                 :: "r"(dst), "l"(tm), "r"(bar), "r"(c0), "r"(c1), "l"(pol) : "memory");
}
constexpr int WP_WQ = 0, WP_W2 = 4, WP_W1 = 6, WP_WO = 8;
__device__ __forceinline__ void issue_weights(const Params& p, uint32_t sb, int m) {
    const int cta = blockIdx.x, h = cta >> 2, j = cta & 3;
    const uint32_t bar = barq(sb, BAR_W + m);
    if (m < WP_W1) tma2d(sb + ST_W2 + (m - WP_W2) * 10240, &p.t2, 160 * j, 64 * h + 32 * (m - WP_W2), bar);
    else if (m < WP_WO) tma2d(sb + ST_W1 + (m - WP_W1) * 10240, &p.t1, 64 * h, 160 * j + 80 * (m - WP_W1), bar);
    else tma2d(sb + ST_WO + (m - WP_WO) * 10240, &p.to, 160 * j, 128 * h + 32 * (m - WP_WO), bar);
}
__device__ __forceinline__ unsigned gtime() { unsigned t; asm volatile("mov.u32 %0, %%globaltimer_lo;" : "=r"(t)); return t; }
#define PW 9
__device__ __forceinline__ bool elect_one() { unsigned r; asm volatile("{\n.reg .pred p;\nelect.sync _|p, 0xffffffff;\nselp.u32 %0, 1, 0, p;\n}" : "=r"(r)); return r; }
__device__ __forceinline__ void issue_reread(const Params& p, uint32_t sb, const char* kbase, int b, int w, int part, u64 pol) {
    const uint32_t bar = barq(sb, BAR_KR + w);
    if (XFLAGS & 2) { if (part == 0 && elect_one()) mbar_arrive(bar); return; }
    if (elect_one()) {
        if (part == 0) mbar_expect_tx(bar, 12288);
        bulk_load(sb + w * 12288 + part * 4096, kbase + b * BSTRIDE + w * 12288 + part * 4096, 4096, bar, pol);
    }
}
__device__ __forceinline__ void role_producer(const Params& p, uint32_t sb, const char* kbase, const char* vbase, unsigned t0) {
    u64 pol_first, pol_norm;
    asm volatile("createpolicy.fractional.L2::evict_first.b64 %0, 1.0;" : "=l"(pol_first));
    asm volatile("createpolicy.fractional.L2::evict_normal.b64 %0, 1.0;" : "=l"(pol_norm));
    STAMP(1);
    auto until = [&](unsigned t) { int it = 0; while ((int)(gtime() - t) < 0 && ++it < 4096) {} };
    const bool mlp = (blockIdx.x >> 2) < NGRP;
    {
        const int lane = threadIdx.x & 31;
        if (lane < 8) { if (lane < 4 && !mlp) mbar_arrive(barq(sb, BAR_W + 4 + lane)); else mbar_expect_tx(barq(sb, BAR_W + 4 + lane), 10240); }
        else if (lane < 8 + 16 - NFIRST) mbar_expect_tx(barq(sb, BAR_FULL + NFIRST + lane - 8), TILE / 2);
        __syncwarp();
    }
    unsigned tnext = t0 + START_T + (((blockIdx.x * 37) & 127) * PACE >> 7);
#pragma unroll 1
    for (int m = 4; m < 12; m++) {
        until(tnext);
        if ((m >= WP_WO || mlp) && elect_one()) issue_weights(p, sb, m);
        tnext += m < WP_WO ? PACE_W1 : PACE_W;
        STAMP(136 + 1 + 2 * m);
    }
    uint32_t pbar = barq(sb, BAR_FULL + 16 - DEPTH), ppar = 0;
    int pleft = DEPTH, pgrp = 1;
    auto gate = [&](uint32_t bar, bool steady) {
        if (steady && elect_one()) mbar_expect_tx(bar, TILE / 2);
        until(tnext);
        if (steady) mbar_wait_or_die(pbar, ppar);
    };
    auto advance = [&](bool steady) {
        tnext += PACE;
        if (steady) {
            pbar += 8;
            if (--pleft == 0) {
                pgrp++;
                pleft = 8;
                const int pb = pgrp >> 1;
                pbar = barq(sb, BAR_FULL + ((pgrp & 1) ? 8 + (pb & 1) * 8 : 0));
                ppar = ((pgrp & 1) ? pb >> 1 : pb) & 1;
            }
        }
    };
#pragma unroll 1
    for (int b = 0; b < NB; b++) {
        const char* ks = kbase + b * BSTRIDE;
        const char* vs = vbase + b * BSTRIDE;
        const int par = b & 1, epar = ((b >> 1) & 1) ^ 1;
        if (b == 1) tnext += PACE_OFF;
#pragma unroll 1
        for (int i = b ? 0 : NFIRST; i < 8; i++) {
            if (b) {
                if (i >= 6) mbar_wait_or_die(barq(sb, BAR_KXE + par * 2 + i - 6), epar);
                else if (i != 2 && i != 5) mbar_wait_or_die(barq(sb, BAR_EMPTY + (i > 2 ? i - 1 : i)), par ^ 1);
            }
            if (!(i & 1)) STAMP(136 + b * 16 + i);
            const uint32_t bar = barq(sb, BAR_FULL + i), dst = sb + i * 8192 + (i >= 6 && par ? OFF_KX - 49152 : 0);
            const u64 pol = (i >= 6 || (XFLAGS & 8)) ? pol_first : pol_norm;
            gate(bar, b);
            if (elect_one()) bulk_load(dst, ks + i * 8192, 8192, bar, pol);
            STAMP(b * 16 + i);
            advance(b);
        }
        if (b < 2) mbar_wait_or_die(barq(sb, BAR_WDONE + b), 0);
#pragma unroll 1
        for (int w = 0; w < 4; w++) {
            const uint32_t bar = barq(sb, BAR_FULL + 8 + par * 8 + 2 * w), dst = sb + (4 + par * 4 + w) * TILE;
            if (b) mbar_wait_or_die(barq(sb, BAR_EMPTY + 4 + par * 4 + w), epar);
            STAMP(136 + b * 16 + 8 + 2 * w);
            gate(bar, b);
            if (elect_one()) bulk_load(dst, vs + w * 12288, 8192, bar, pol_first);
            STAMP(b * 16 + 8 + 2 * w);
            advance(b);
            gate(bar + 8, b);
            if (elect_one()) {
                bulk_load(dst + 8192, vs + w * 12288 + 8192, 4096, bar + 8, pol_first);
                bulk_load(dst + 12288, vs + 49152 + w * 4096, 4096, bar + 8, pol_first);
            }
            STAMP(b * 16 + 9 + 2 * w);
            advance(b);
        }
    }
#pragma unroll 1
    for (int w = 0; w < 4; w++) {
        mbar_wait_or_die(barq(sb, BAR_EMPTY + w), (NB & 1) ^ 1);
#pragma unroll 1
        for (int part = 0; part < 3; part++) { issue_reread(p, sb, kbase, NB - 1, w, part, pol_first); delay(TAILGAP); }
    }
    mbar_wait_or_die(barq(sb, BAR_DONE), 0);
}

__device__ __forceinline__ unsigned tagf(float x, unsigned tag) { unsigned r; asm("lop3.b32 %0, %1, 0xfffffffc, %2, 0xea;" : "=r"(r) : "r"(__float_as_uint(x)), "r"(tag)); return r; }
__device__ __forceinline__ uint4 pkt(float x, float y, float z, float w, unsigned tag) {
    return make_uint4(__float_as_uint(x), __float_as_uint(y), __float_as_uint(z), tagf(w, tag));
}
__device__ __forceinline__ float4 pksum(const uint4& a, const uint4& b, const uint4& c, const uint4& d) {
    return make_float4((__uint_as_float(a.x) + __uint_as_float(b.x)) + (__uint_as_float(c.x) + __uint_as_float(d.x)),
                       (__uint_as_float(a.y) + __uint_as_float(b.y)) + (__uint_as_float(c.y) + __uint_as_float(d.y)),
                       (__uint_as_float(a.z) + __uint_as_float(b.z)) + (__uint_as_float(c.z) + __uint_as_float(d.z)),
                       (__uint_as_float(a.w) + __uint_as_float(b.w)) + (__uint_as_float(c.w) + __uint_as_float(d.w)));
}
__device__ __forceinline__ float rsq(float x) { float r; asm("rsqrt.approx.ftz.f32 %0, %1;" : "=f"(r) : "f"(x)); return r; }
__device__ __forceinline__ float rcp(float x) { float r; asm("rcp.approx.ftz.f32 %0, %1;" : "=f"(r) : "f"(x)); return r; }
__device__ __forceinline__ void store_q(uint32_t sb, int qslot, int lane, float4 u, float4 cs, float mu, float rs) {
    const uint32_t qa = sb + OFF_Q + qslot * QSLOT + ((lane >> 1) & 3) * 32 + (lane >> 3) * 8 + (lane & 1) * 4;
    sts32(qa, pack_bf16((u.x - mu * cs.x) * rs, (u.y - mu * cs.y) * rs));
    sts32(qa + 144, pack_bf16((u.z - mu * cs.z) * rs, (u.w - mu * cs.w) * rs));
}

struct AttCtx {
    uint32_t sb;
    int w, lane, g, t;
    unsigned sel0, sel1;
    uint32_t pst, qoff;
};

#define SCHED_FENCE(i) fv[i] = clk()
template <class G0, class G1>
__device__ __forceinline__ void softmax_part(const AttCtx& c, const float (&v)[8], float& m_out, unsigned& pp_out, G0 gap0, G1 gap1) {
    const bool ph = (c.t ^ c.g) & 1, hi = c.t >> 1;
    float u0 = ph ? v[1] : v[0], u1 = ph ? v[3] : v[2], u2 = ph ? v[5] : v[4], u3 = ph ? v[7] : v[6];
    const float sc = 0.08838834764831845f * 1.4426950408889634f;
    float s0 = (hi ? u2 : u0) * sc, s1 = (hi ? u3 : u1) * sc;
    float mx = fmaxf(s0, s1);
    int mi = __float_as_int(mx); mi ^= (mi >> 31) & 0x7fffffff;
    gap0();
    mi = __reduce_max_sync(0xffffffffu, mi);
    mi ^= (mi >> 31) & 0x7fffffff;
    const float m = __int_as_float(mi);
    const float e0 = ex2(s0 - m), e1 = ex2(s1 - m);
    gap1();
    const unsigned pp = pack_bf16(e0, e1);
    sts16(c.pst, pp & 0xffffu);
    sts16(c.pst + 32, pp >> 16);
    m_out = m; pp_out = pp;
    __syncwarp();
}
__device__ __forceinline__ unsigned sum_p(unsigned pp) {
    return __reduce_add_sync(0xffffffffu, __float2uint_rn((__uint_as_float(pp << 16) + __uint_as_float(pp & 0xffff0000u)) * 16777216.0f));
}
__device__ __forceinline__ void publish_ml(const AttCtx& c, int slot, float m, unsigned li) {
    if (c.lane == 0) { sts64f(c.sb + OFF_ML + slot * 32 + c.w * 8, m, __uint_as_float(li)); mbar_arrive(barq(c.sb, BAR_ML + slot)); }
}

__device__ __forceinline__ void load_q(const AttCtx& c, int qslot, uint2 (&qf)[4]) {
    const uint32_t qa = c.qoff + qslot * QSLOT;
#pragma unroll
    for (int j = 0; j < 4; j++) qf[j] = lds64((j & 1 ? qa ^ 8 : qa) + (j >> 1) * 16);
}

template <int NT>
__device__ __forceinline__ void qk_tiles(const uint4 (*kr)[4], const uint2 (&qf)[4], float* v) {
    float acc[NT][4];
#pragma unroll
    for (int mt = 0; mt < NT; mt++) { acc[mt][0] = acc[mt][1] = acc[mt][2] = acc[mt][3] = 0.f; }
#pragma unroll
    for (int j = 0; j < 4; j++)
#pragma unroll
        for (int mt = 0; mt < NT; mt++) mma(acc[mt], kr[mt][j].x, kr[mt][j].y, kr[mt][j].z, kr[mt][j].w, qf[j].x, qf[j].y);
#pragma unroll
    for (int mt = 0; mt < NT; mt++) v[mt] = acc[mt][0] + acc[mt][3];
}
template <int NT>
__device__ __forceinline__ void k_from_smem(uint4 (*kr)[4], uint32_t aE, uint32_t aO) {
#pragma unroll
    for (int j = 0; j < 4; j++)
#pragma unroll
        for (int mt = 0; mt < NT; mt++) kr[mt][j] = lds128((((j ^ mt) & 1) ? aO : aE) + mt * 2048 + (j >> 1) * 128);
}

template <int I0, int I1>
__device__ __forceinline__ void v_load(uint4 (&vr)[16], uint32_t va) {
#pragma unroll
    for (int i = I0; i < I1; i++) { const uint2 a = lds64(va + i * 512), b = lds64(va + i * 512 + 256); vr[i] = make_uint4(a.x, a.y, b.x, b.y); }
}
template <int I0, int I1>
__device__ __forceinline__ void pv_regs(const AttCtx& c, float (&o)[4][4], const uint4 (&vr)[16], const uint4* pw) {
#pragma unroll
    for (int i = I0; i < I1; i++) {
        const unsigned pv[4] = {pw[i].x, pw[i].y, pw[i].z, pw[i].w};
#pragma unroll
        for (int k = 0; k < 4; k++)
            mma(o[k], vr[i * 4 + k].x, vr[i * 4 + k].y, vr[i * 4 + k].z, vr[i * 4 + k].w, __byte_perm(pv[k], 0, c.sel0), __byte_perm(pv[k], 0, c.sel1));
    }
}
__device__ __forceinline__ void pv_half(const AttCtx& c, float (&o)[4][4], uint32_t va, uint32_t pa) {
#pragma unroll
    for (int i = 0; i < 4; i++) {
        const uint4 pw = lds128(pa + i * 16);
        const unsigned pv[4] = {pw.x, pw.y, pw.z, pw.w};
#pragma unroll
        for (int k = 0; k < 4; k++) {
            const uint2 a = lds64(va + (i * 8 + k * 2) * 256), b = lds64(va + (i * 8 + k * 2 + 1) * 256);
            mma(o[k], a.x, a.y, b.x, b.y, __byte_perm(pv[k], 0, c.sel0), __byte_perm(pv[k], 0, c.sel1));
        }
    }
}
__device__ __forceinline__ void publish_part(const AttCtx& c, const float (&o)[4][4], int slot) {
    sts128f(c.sb + OFF_PART + slot * 2048 + c.w * 512 + c.lane * 16,
            (o[0][0] + o[1][0]) + (o[2][0] + o[3][0]), (o[0][1] + o[1][1]) + (o[2][1] + o[3][1]),
            (o[0][2] + o[1][2]) + (o[2][2] + o[3][2]), (o[0][3] + o[1][3]) + (o[2][3] + o[3][3]));
    nb_arrive(NB_PART + slot);
}

#undef PW
#define PW w
__device__ __forceinline__ void role_att(const Params& p, uint32_t sb, const char* kbase, int w) {
    u64 pol_first;
    asm volatile("createpolicy.fractional.L2::evict_first.b64 %0, 1.0;" : "=l"(pol_first));
    AttCtx c;
    c.sb = sb; c.w = w; c.lane = threadIdx.x & 31; c.g = c.lane >> 2; c.t = c.lane & 3;
    const bool act = (c.g >> 1) == c.t;
    c.sel0 = act ? ((c.g & 1) ? 0x1044u : 0x4410u) : 0x4444u;
    c.sel1 = act ? ((c.g & 1) ? 0x3244u : 0x4432u) : 0x4444u;
    c.pst = sb + OFF_P + c.w * 128 + ((((c.t ^ c.g) & 1) + 4 * (c.t >> 1)) * 8 + c.g) * 2;
    c.qoff = sb + OFF_Q + (c.g & 1) * 144 + c.t * 32 + ((c.g >> 1) & 1) * 8;
    asm volatile("" : "+r"(c.pst), "+r"(c.qoff), "+r"(c.sel0), "+r"(c.sel1));
    const uint32_t offE = c.g * 256 + c.t * 16 + 64 * (c.g & 1);
    const uint32_t kE = sb + c.w * 12288 + offE, kO = kE ^ 64;
    const uint32_t xE0 = sb + c.w * 4096 + offE;
    const uint32_t pa = sb + OFF_P + c.w * 128;
    const uint32_t barkr = barq(sb, BAR_KR + c.w);
    {
        const int lane = c.lane;
        float mu0, rs0;
        {
            float s1 = 0.f, s2 = 0.f;
#pragma unroll
            for (int u = 0; u < 5; u++) {
                const uint4 y = __ldg((const uint4*)(p.x + (2 * w + (lane >> 4)) * DM + 128 * u + 8 * (lane & 15)));
                const unsigned yy[4] = {y.x, y.y, y.z, y.w};
#pragma unroll
                for (int i = 0; i < 4; i++) {
                    const float x0 = __uint_as_float(yy[i] << 16), x1 = __uint_as_float(yy[i] & 0xffff0000u);
                    s1 += x0 + x1; s2 += fmaf(x0, x0, x1 * x1);
                }
            }
#pragma unroll
            for (int o = 8; o; o >>= 1) { s1 += __shfl_xor_sync(0xffffffffu, s1, o); s2 += __shfl_xor_sync(0xffffffffu, s2, o); }
            mu0 = s1 * (1.0f / DM);
            rs0 = rsq(fmaxf(s2 * (1.0f / DM) - mu0 * mu0, 0.f) + 1e-5f);
        }
        STAMP(128);
        mbar_wait(barq(sb, BAR_WDONE), 0);
        STAMP(129);
        const unsigned char* a = xbase() + (blockIdx.x >> 2) * 65536 + lane * 16;
        const unsigned char* a1 = a + (w & 1) * 16384 + (w >> 1) * 4096;
        uint4 r[3][4];
        int it = 0;
        while (true) {
            unsigned d = 0;
#pragma unroll
            for (int i = 0; i < 4; i++) { r[0][i] = ld_rlx128(a + Q_OFF + i * 1024); r[1][i] = ld_rlx128(a1 + i * 1024); r[2][i] = ld_rlx128(a1 + 512 + i * 1024); }
#pragma unroll
            for (int i = 0; i < 4; i++) d |= (r[0][i].w ^ 2u) | (r[1][i].w ^ 2u) | (r[2][i].w ^ 2u);
            if (__all_sync(0xffffffffu, (d & 3u) == 0)) break;
            if (++it > SPIN_LIMIT) bail();
        }
        const float4 cs = pksum(r[0][0], r[0][1], r[0][2], r[0][3]);
        if (w == 0) sts128f(sb + OFF_CSQ + lane * 16, cs.x, cs.y, cs.z, cs.w);
#pragma unroll
        for (int k = 0; k < 2; k++)
            store_q(sb, 2 * w + k, lane, pksum(r[1 + k][0], r[1 + k][1], r[1 + k][2], r[1 + k][3]), cs, __shfl_sync(0xffffffffu, mu0, k * 16), __shfl_sync(0xffffffffu, rs0, k * 16));
        __syncwarp();
        if (lane == 0) mbar_arrive(barq(sb, BAR_Q1));
        STAMP(130);
    }
    mbar_wait(barq(sb, BAR_Q1), 0);
    unsigned fz = 0;

#pragma unroll 1
    for (int b = 0; b <= NB; b++) {
        uint2 qf[4];
        float v[8], o[4][4], m;
        unsigned pp;
        if (b < NB) {
            load_q(c, b, qf);
            {
                const int p0 = c.w + (c.w >> 1);
                mbar_wait(barq(sb, BAR_FULL + p0), b & 1);
                mbar_wait(barq(sb, BAR_FULL + p0 + 1), b & 1);
                uint4 kr[6][4];
                k_from_smem<6>(kr, kE, kO);
                qk_tiles<6>(kr, qf, v);
            }
            __syncwarp();
            if (b == 0 && c.lane == 0) mbar_arrive(barq(sb, BAR_EMPTY + c.w));
            auto reread = [&]() {
#pragma unroll 1
                for (int part = 0; part < 3; part++) {
                    const int pos = 3 * c.w + part + RRLEAD;
                    if (pos >= 8) mbar_wait(barq(sb, BAR_FULL + (b & 1) * 8 + pos), (b >> 1) & 1);
                    else mbar_wait(barq(sb, BAR_FULL + pos), b & 1);
                    issue_reread(p, sb, kbase, b - 1, c.w, part, pol_first);
                }
            };
            if (b && c.w < 2) reread();
            {
                mbar_wait(barq(sb, BAR_FULL + 6 + (c.w >> 1)), b & 1);
                uint4 kr[2][4];
                k_from_smem<2>(kr, xE0 + kx_off(b & 1), (xE0 + kx_off(b & 1)) ^ 64);
                qk_tiles<2>(kr, qf, v + 6);
            }
            STAMP(b * 16 + 0);
            softmax_part(c, v, m, pp, []() {}, []() {});
            publish_ml(c, b & 1, m, sum_p(pp));
            if (b && c.w >= 2) reread();
        }
        if (b < NB) {
            STAMP(b * 16 + 1);
            const int vs = 4 + (b & 1) * 4 + c.w;
#pragma unroll
            for (int i = 0; i < 4; i++) { o[i][0] = o[i][1] = o[i][2] = o[i][3] = 0.f; }
#pragma unroll
            for (int hh = 0; hh < 2; hh++) {
                mbar_wait(barq(sb, BAR_FULL + vs * 2 + hh), (b >> 1) & 1);
                if (hh) STAMP(b * 16 + 2);
                pv_half(c, o, sb + vs * TILE + hh * 8192 + c.lane * 8, pa + hh * 64);
            }
            publish_part(c, o, b & 1);
            STAMP(b * 16 + 3);
        }
        if (b > 0) {
            const int b2 = b - 1;
            const int vs = 4 + (b2 & 1) * 4 + c.w;
            const uint32_t va = sb + vs * TILE + c.lane * 8;
            const uint32_t xE = xE0 + kx_off(b2 & 1), xO = xE ^ 64;
            uint4 kr[6][4];
            mbar_wait(barkr, b2 & 1);
            k_from_smem<6>(kr, kE, kO);
            asm volatile("" :: "r"(kr[5][3].x), "r"(kr[4][3].x), "r"(kr[3][3].x), "r"(kr[2][3].x), "r"(kr[1][3].x), "r"(kr[0][3].x) : "memory");
            __syncwarp();
            if (c.lane == 0) mbar_arrive(barq(sb, BAR_EMPTY + c.w));
            STAMP(b2 * 16 + 4);
            if (b == NB) { nb_sync(NB_QLAST); if (c.lane == 0) mbar_arrive(barq(sb, BAR_DONE)); }
            else mbar_wait(barq(sb, BAR_Q2 + (b2 & 1)), (b2 >> 1) & 1);
            STAMP(b2 * 16 + 5);
            load_q(c, 8 + (b2 & 1), qf);
            uint4 kx[2][4], vr[16];
            float acc[4][4];
            unsigned fv[15];
#pragma unroll
            for (int jj = 0; jj < 4; jj++) {
#pragma unroll
                for (int mt = 0; mt < 4; mt++) {
                    if (jj == 0) { acc[mt][0] = acc[mt][1] = acc[mt][2] = acc[mt][3] = 0.f; }
                    mma(acc[mt], kr[mt][jj].x, kr[mt][jj].y, kr[mt][jj].z, kr[mt][jj].w, qf[jj].x, qf[jj].y);
                }
                kx[0][jj] = lds128(((jj & 1) ? xO : xE) + (jj >> 1) * 128);
                kx[1][jj] = lds128(((jj & 1) ? xE : xO) + 2048 + (jj >> 1) * 128);
                SCHED_FENCE(jj);
            }
            float acd[4][4];
#pragma unroll
            for (int jj = 0; jj < 4; jj++) {
#pragma unroll
                for (int mt = 0; mt < 4; mt++) {
                    if (jj == 0) { acd[mt][0] = acd[mt][1] = acd[mt][2] = acd[mt][3] = 0.f; }
                    const uint4& a = mt < 2 ? kr[4 + mt][jj] : kx[mt - 2][jj];
                    mma(acd[mt], a.x, a.y, a.z, a.w, qf[jj].x, qf[jj].y);
                }
                if (jj == 0) v_load<0, 1>(vr, va);
                if (jj == 1) v_load<1, 3>(vr, va);
                if (jj == 2) v_load<3, 5>(vr, va);
                if (jj == 3) v_load<5, 8>(vr, va);
                if (jj == 1) {
#pragma unroll
                    for (int mt = 0; mt < 4; mt++) v[mt] = acc[mt][0] + acc[mt][3];
                }
                SCHED_FENCE(4 + jj);
            }
#pragma unroll
            for (int mt = 0; mt < 4; mt++) v[4 + mt] = acd[mt][0] + acd[mt][3];
            softmax_part(c, v, m, pp, [&]() { v_load<8, 13>(vr, va); SCHED_FENCE(8); }, [&]() { v_load<13, 16>(vr, va); SCHED_FENCE(9); });
            STAMP(b2 * 16 + 6);
#pragma unroll
            for (int i = 0; i < 4; i++) { o[i][0] = o[i][1] = o[i][2] = o[i][3] = 0.f; }
            uint4 vs2[16], pw[8];
#pragma unroll
            for (int i = 0; i < 4; i++) pw[i] = lds128(pa + i * 16);
            v_load<0, 3>(vs2, va + 8192);
            const unsigned li = sum_p(pp);
            SCHED_FENCE(10);
            publish_ml(c, 2 + (b2 & 1), m, li);
            if (c.lane == 0) mbar_arrive(barq(sb, BAR_KXE + (b2 & 1) * 2 + (c.w >> 1)));
            pv_regs<0, 2>(c, o, vr, pw);
            v_load<3, 7>(vs2, va + 8192);
            pw[4] = lds128(pa + 64); pw[5] = lds128(pa + 80);
            SCHED_FENCE(11);
            pv_regs<2, 4>(c, o, vr, pw);
            v_load<7, 12>(vs2, va + 8192);
            pw[6] = lds128(pa + 96); pw[7] = lds128(pa + 112);
            SCHED_FENCE(12);
            v_load<12, 16>(vs2, va + 8192);
            pv_regs<0, 2>(c, o, vs2, pw + 4);
            SCHED_FENCE(13);
            pv_regs<2, 4>(c, o, vs2, pw + 4);
            publish_part(c, o, 2 + (b2 & 1));
            SCHED_FENCE(14);
#pragma unroll
            for (int i = 0; i < 15; i++) fz ^= fv[i];
            if (c.lane == 0) mbar_arrive(barq(sb, BAR_EMPTY + vs));
            STAMP(b2 * 16 + 7);
        }
    }
    sts32(pa, fz);
}

__device__ __forceinline__ unsigned char* gptr(unsigned lo, unsigned hi) { u64 r; asm("mov.b64 %0, {%1, %2};" : "=l"(r) : "r"(lo), "r"(hi)); return (unsigned char*)r; }
template <class BAD>
__device__ __forceinline__ void poll(unsigned first, BAD bad) {
    delay(first);
    int it = 0;
    bool again;
    do { const bool more = ++it < SPIN_LIMIT; again = __any_sync(0xffffffffu, bad() && more); } while (again);
}
__device__ __forceinline__ unsigned or3x(unsigned a, unsigned b, unsigned t) { unsigned r; asm("lop3.b32 %0, %1, %2, %3, 0x7e;" : "=r"(r) : "r"(a), "r"(t), "r"(b)); return r; }
__device__ __forceinline__ unsigned or3(unsigned a, unsigned b, unsigned c) { unsigned r; asm("lop3.b32 %0, %1, %2, %3, 0xfe;" : "=r"(r) : "r"(a), "r"(b), "r"(c)); return r; }
struct Rec4 { uint4 a0, a1, a2, a3, m, n; };
__device__ __forceinline__ void poll4(const unsigned char* ra, const unsigned char* rm, unsigned tag, unsigned first, Rec4& x) {
    poll(first, [&]() {
        x.m = ld_rlx128(rm); x.n = ld_rlx128(rm + 16);
        x.a0 = ld_rlx128(ra); x.a1 = ld_rlx128(ra + 1024); x.a2 = ld_rlx128(ra + 2048); x.a3 = ld_rlx128(ra + 3072);
        return ((or3(or3x(x.m.y, x.m.w, tag), or3x(x.n.y, x.n.w, tag), or3x(x.a0.w, x.a1.w, tag)) | or3x(x.a2.w, x.a3.w, tag)) & 3u) != 0;
    });
}

__device__ __forceinline__ unsigned poll_x(const unsigned char* a, unsigned expect, unsigned first, u64 (&r)[5], uint32_t dst, int ln, int bar, float& s1, float& s2) {
    poll(first, [&]() {
#pragma unroll
        for (int v = 0; v < 5; v++) r[v] = ld_rlx64(a + voff(v));
        return (or3(or3x((unsigned)r[0], (unsigned)r[1], expect), or3x((unsigned)r[2], (unsigned)r[3], expect), (unsigned)r[4] ^ expect) & 1023u) != 0;
    });
    const unsigned w0 = pack_bf16(from_fix(r[0]), from_fix(r[1])), w1 = pack_bf16(from_fix(r[2]), from_fix(r[3])), w2 = pack_bf16(from_fix(r[4]), 0.f);
    sts32(dst + ln * 4, w0);
    sts32(dst + 128 + ln * 4, w1);
    sts16(dst + 256 + ln * 2, w2);
    nb_arrive(bar);
    const unsigned fence = clk();
    const float x0 = __uint_as_float(w0 << 16), x1 = __uint_as_float(w0 & 0xffff0000u), x2 = __uint_as_float(w1 << 16),
                x3 = __uint_as_float(w1 & 0xffff0000u), x4 = __uint_as_float(w2 << 16);
    s1 = ((x0 + x1) + (x2 + x3)) + x4;
    s2 = fmaf(x4, x4, fmaf(x0, x0, x1 * x1) + fmaf(x2, x2, x3 * x3));
#pragma unroll
    for (int o = 16; o; o >>= 1) { s1 += __shfl_xor_sync(0xffffffffu, s1, o); s2 += __shfl_xor_sync(0xffffffffu, s2, o); }
    return fence;
}
__device__ __forceinline__ uint32_t xoff(int v, int l) { return v < 4 ? (v >> 1) * 128 + l * 4 + (v & 1) * 2 : 256 + l * 2; }
__device__ __forceinline__ constexpr int krow(int s, int e) { return s < 8 ? 64 * (s >> 2) + 16 * ((s >> 1) & 1) + 2 * (s & 1) + e : 128 + 4 * (s & 1) + 2 * e; }
__device__ __forceinline__ constexpr int kstep_t(int s) { return s < 8 ? 4 : 8; }
__device__ __forceinline__ constexpr int kpair(int s) { return s < 8 ? 32 : 1; }

#undef PW
#define PW (6 + cw)
__device__ __forceinline__ void role_chain(const Params& p, uint32_t sb, int cw) {
    const int lane = threadIdx.x & 31, cta = blockIdx.x, h = cta >> 2, j = cta & 3;
    int layer = cw >> 1;
    const bool mlp = h < NGRP;
    unsigned char* const S = xbase();
    unsigned char* const grp = S + h * 65536;
    const int cv = (lane & 7) < 5 ? (lane & 7) : 0;
    unsigned char* const cadr = S + AR_OFF + j * 65536 + (h >> 3) * 1024 + (h & 7) * 8 + voff(cv) + (lane >> 3) * 4096;
    const int ccol = 160 * j + 32 * cv + h;
    const float b2v = bf16_val(ldg16(p.b2 + ccol));
    unsigned resA = 0, resB = 0;
    if (!layer) {
        const __nv_bfloat16* xp = p.x + cw * DM + ccol;
        resA = ldg16(xp) | (ldg16(xp + 2 * DM) << 16); resB = ldg16(xp + 4 * DM) | (ldg16(xp + 6 * DM) << 16);
    }
    unsigned b1p = 0;
    if (mlp) b1p = ldg32(p.b1 + 64 * h + 2 * lane);
    if (cw == 1 && h < 20) {
        unsigned char* a = S + AR_OFF + j * 65536 + (h & 3) * 1024 + voff(h >> 2) + lane * 16;
        st_rlx128(a, make_uint4(0u, 0u, 0u, 0u)); st_rlx128(a + 4096, make_uint4(0u, 0u, 0u, 0u));
        asm volatile("fence.acq_rel.gpu;" ::: "memory");
        __syncwarp();
        if (lane < 2) st_rlx128(S + FLAG_OFF + j * 1024 + h * 32 + lane * 16, make_uint4(1u, 1u, 1u, 1u));
    }
    if (cw == 2) {
        unsigned char* const flag = S + FLAG_OFF + j * 1024;
        if (lane < 24) st_rlx64(grp + (lane < 16 ? M_OFF + (lane >> 3) * 16384 : QS_OFF) + ((lane >> 2) & 1) * 4096 + (lane & 3) * 32 + j * 8, 0u, 0u);
        sts128f(sb + OFF_PREV + lane * 16, 0.f, 0.f, 0.f, 0.f);
        __syncwarp();
        mbar_wait(barq(sb, BAR_Q1), 0);
        unsigned best0 = ~0u, best1 = ~0u;
#pragma unroll 1
        for (int i = 0; i < 24; i++) {
            const unsigned t0 = clk();
            unsigned v, t1;
            asm volatile("{\n.reg .pred p;\nsetp.eq.u32 p, %2, 0;\nmov.u32 %0, 0;\n@p atom.relaxed.gpu.global.exch.b32 %0, [%1], 1;\n}"
                         : "=r"(v) : "l"(grp + QS_OFF + 64 + j * 8 + (i & 1) * 4096), "r"(lane) : "memory");
            asm volatile("and.b32 %0, %1, 0x80000000;" : "=r"(t1) : "r"(v) : "memory");
            t1 += clk();
            const unsigned dt = __shfl_sync(0xffffffffu, t1 - t0, 0);
            if (i & 1) best1 = min(best1, dt); else best0 = min(best0, dt);
            if (i >= 3 && min(best0, best1) < 390u && max(best0, best1) > min(best0, best1) + 90u) break;
        }
        const unsigned nb = best1 < best0;
        sts32(sb + OFF_NEAR, nb);
        STAMP(133);
        int it = 0;
        if (mlp) {
            mbar_wait(barq(sb, BAR_WDONE + 1), 0);
            const unsigned char* ru = grp + U_OFF + nb * 4096 + (lane >> 3) * 128 + (lane & 7) * 8;
            uint2 u0, u1, u2, u3;
            while (true) {
                u0 = ld_rlx64v(ru); u1 = ld_rlx64v(ru + 512); u2 = ld_rlx64v(ru + 1024); u3 = ld_rlx64v(ru + 1536);
                if (__all_sync(0xffffffffu, (((u0.y ^ 2u) | (u1.y ^ 2u) | (u2.y ^ 2u) | (u3.y ^ 2u)) & 3u) == 0)) break;
                if (++it > SPIN_LIMIT) bail();
            }
            sts64f(sb + OFF_CS1 + lane * 8, (__uint_as_float(u0.x) + __uint_as_float(u1.x)) + (__uint_as_float(u2.x) + __uint_as_float(u3.x)),
                   (__uint_as_float(u0.y) + __uint_as_float(u1.y)) + (__uint_as_float(u2.y) + __uint_as_float(u3.y)));
        }
        STAMP(134);
        if (lane < 2) st_rlx64(grp + M_OFF + j * 8 + lane * 4096, 0u, 2u);
        while (true) {
            unsigned f0;
            asm volatile("ld.acquire.gpu.global.u32 %0, [%1];" : "=r"(f0) : "l"(flag + (lane < 20 ? lane : 0) * 32) : "memory");
            const uint2 f1 = ld_rlx64v(grp + M_OFF + nb * 4096 + (lane & 3) * 8);
            if (__all_sync(0xffffffffu, f0 == 1u && (f1.y & 3u) != 0)) break;
            if (++it > SPIN_LIMIT) bail();
        }
        __syncwarp();
        if (lane == 0) mbar_arrive(barq(sb, BAR_NEAR));
    }
    mbar_wait(barq(sb, BAR_NEAR), 0);
    constexpr unsigned PMASK = (1u << 13) | (1u << 16) | (1u << 17) | (1u << 19);
    const unsigned nb = __shfl_sync(0xffffffffu, lds32(sb + OFF_NEAR), 0);
    const unsigned shi = (unsigned)((size_t)S >> 32), slo = (unsigned)(size_t)S;
    const unsigned ngr = nb << 12;
    const unsigned nar = ((nb ^ __popc(((AR_OFF + j * 65536) ^ (h * 65536)) & PMASK)) & 1) << 12;
    const unsigned arb = slo + AR_OFF + j * 65536;
    const unsigned clo = (unsigned)(size_t)cadr;
    STAMP(135);
#define GP(lo) gptr(lo, shi)
#define FRESH_LANE() int ln = lane; asm volatile("" : "+r"(ln))
#define F(x) __uint_as_float(x)
#define U(x) __uint2float_rn(__float_as_uint(x))

#pragma unroll 1
    for (int b = layer ? 0 : cw; b < NB - (cw >> 1); b += 2 - layer) {
        const int slot = layer * 2 + (b & 1), use = b >> 1;
        const unsigned tag = (use + 1) & 3, cbase = (use & 1) * 512;
        const unsigned gb = slo + h * 65536 + (b & 1) * 16384;
        {
            FRESH_LANE();
            const unsigned l16 = (ln >> 2) * 128 + (ln & 3) * 16;
            unsigned char* const wa = GP(gb + j * 1024 + layer * 64 + l16 + ngr);
            unsigned char* const wb = GP(gb + j * 1024 + layer * 64 + l16 + (ngr ^ 4096));
            unsigned char* const wm = GP(gb + M_OFF + layer * 32 + j * 8 + ln * 4096);
            const unsigned char* const ra = GP(gb + ngr + layer * 64 + l16);
            const unsigned char* const rm = GP(gb + ngr + M_OFF + layer * 32);
            const uint32_t pa = sb + OFF_PART + slot * 2048 + ln * 16;
            mbar_wait(barq(sb, BAR_ML + slot), use & 1);
            const float4 ml0 = lds128f(sb + OFF_ML + slot * 32), ml1 = lds128f(sb + OFF_ML + slot * 32 + 16);
            const float M = fmaxf(fmaxf(ml0.x, ml0.z), fmaxf(ml1.x, ml1.z));
            const float e0 = ex2(ml0.x - M), e1 = ex2(ml0.z - M), e2 = ex2(ml1.x - M), e3 = ex2(ml1.z - M);
            st_rlx64_if(ln < 2, wm, __float_as_uint(M), tagf(((e0 * U(ml0.y) + e1 * U(ml0.w)) + (e2 * U(ml1.y) + e3 * U(ml1.w))) * (1.0f / 16777216.0f), tag));
            nb_sync(NB_PART + slot);
            STAMP(b * 16 + 0);
            const float4 p0 = lds128f(pa), p1 = lds128f(pa + 512), p2 = lds128f(pa + 1024), p3 = lds128f(pa + 1536);
            const uint4 pk = pkt((e0 * p0.x + e1 * p1.x) + (e2 * p2.x + e3 * p3.x), (e0 * p0.y + e1 * p1.y) + (e2 * p2.y + e3 * p3.y),
                                 (e0 * p0.z + e1 * p1.z) + (e2 * p2.z + e3 * p3.z), (e0 * p0.w + e1 * p1.w) + (e2 * p2.w + e3 * p3.w), tag);
            st_rlx128(wa, pk);
            st_rlx128(wb, pk);
            Rec4 r;
            poll(0, [&]() { r.m = ld_rlx128(rm); r.n = ld_rlx128(rm + 16); return ((or3x(r.m.y, r.m.w, tag) | or3x(r.n.y, r.n.w, tag)) & 3u) != 0; });
            r.a0 = ld_rlx128(ra); r.a1 = ld_rlx128(ra + 1024); r.a2 = ld_rlx128(ra + 2048); r.a3 = ld_rlx128(ra + 3072);
            if ((ln & 7) < 5 && ln < 16) {
                const unsigned res = layer ? lds16(sb + OFF_X2 + (b & 1) * 320 + xoff(ln & 7, h)) : (((use & 2) ? resB : resA) >> ((use & 1) * 16)) & 0xffffu;
                red64(GP(clo + boff(slot)), to_fix(bf16_val(res)) + cbase - lds64u(sb + OFF_PREV + slot * 64 + (ln & 7) * 8));
            }
            const float Mg = fmaxf(fmaxf(F(r.m.x), F(r.m.z)), fmaxf(F(r.n.x), F(r.n.z)));
            float f0 = ex2(F(r.m.x) - Mg), f1 = ex2(F(r.m.z) - Mg), f2 = ex2(F(r.n.x) - Mg), f3 = ex2(F(r.n.z) - Mg);
            const float inv = rcp(((f0 * F(r.m.y) + f1 * F(r.m.w)) + (f2 * F(r.n.y) + f3 * F(r.n.w))) * (1.0f / FIX_SCALE));
            f0 *= inv; f1 *= inv; f2 *= inv; f3 *= inv;
            asm volatile("" : "+f"(f0), "+f"(f1), "+f"(f2), "+f"(f3));
            if (__any_sync(0xffffffffu, ((or3x(r.a0.w, r.a1.w, tag) | or3x(r.a2.w, r.a3.w, tag)) & 3u) != 0))
                poll(0, [&]() {
                    r.a0 = ld_rlx128(ra); r.a1 = ld_rlx128(ra + 1024); r.a2 = ld_rlx128(ra + 2048); r.a3 = ld_rlx128(ra + 3072);
                    return ((or3x(r.a0.w, r.a1.w, tag) | or3x(r.a2.w, r.a3.w, tag)) & 3u) != 0;
                });
            STAMP(b * 16 + 1);
            const float gx = (f0 * F(r.a0.x) + f1 * F(r.a1.x)) + (f2 * F(r.a2.x) + f3 * F(r.a3.x));
            const float gy = (f0 * F(r.a0.y) + f1 * F(r.a1.y)) + (f2 * F(r.a2.y) + f3 * F(r.a3.y));
            const float gz = (f0 * F(r.a0.z) + f1 * F(r.a1.z)) + (f2 * F(r.a2.z) + f3 * F(r.a3.z));
            const float gw = (f0 * F(r.a0.w) + f1 * F(r.a1.w)) + (f2 * F(r.a2.w) + f3 * F(r.a3.w));
            sts64u(sb + OFF_O + cw * 256 + ln * 8, (u64)pack_bf16(gx, gy) | ((u64)pack_bf16(gz, gw) << 32));
            nb_arrive(NB_O + cw);
        }
        STAMP(b * 16 + 2);
        {
            FRESH_LANE();
            const unsigned char* const ra = GP(arb + nar + boff(slot) + (ln >> 3) * 1024 + (ln & 7) * 8);
            unsigned char* const wm = GP(gb + M_OFF + 64 + layer * 32 + j * 8 + ln * 4096);
            u64 r[5];
            float s1, s2;
            delay(DELAY_AR1);
            const unsigned fence = poll_x(ra, cbase + CNT1, 0, r, sb + OFF_X1 + cw * 320, ln, NB_X1 + cw, s1, s2);
            STAMP(b * 16 + 3);
            if (ln < 2 && mlp) st_rlx64(wm, __float_as_uint(s1), tagf(s2, tag));
            if ((ln & 7) < 5 && ln < 16)
                red64(GP(clo + 256 + boff(slot)), to_fix(bf16_val(lds16(sb + OFF_X1 + cw * 320 + xoff(ln & 7, h))) + b2v) + cbase
                                                      - lds64u(sb + OFF_PREV + (4 + slot) * 64 + (ln & 7) * 8));
            if (ln == h) {
#pragma unroll
                for (int v = 0; v < 5; v++) sts64u(sb + OFF_PREV + slot * 64 + v * 8, r[v]);
                sts32(sb + OFF_PREV + slot * 64 + 56, fence);
            }
        }
        if (mlp) {
            FRESH_LANE();
            const unsigned char* const ru = GP(gb + ngr + U_OFF + layer * 64 + (ln >> 3) * 128 + (ln & 7) * 8);
            const unsigned char* const rm = GP(gb + ngr + M_OFF + 64 + layer * 32);
            const float2 cs1 = lds64f(sb + OFF_CS1 + ln * 8);
            struct { uint2 u0, u1, u2, u3; uint4 m, n; } r;
            delay(DELAY_U);
            poll(0, [&]() {
                r.m = ld_rlx128(rm); r.n = ld_rlx128(rm + 16);
                r.u0 = ld_rlx64v(ru); r.u1 = ld_rlx64v(ru + 512); r.u2 = ld_rlx64v(ru + 1024); r.u3 = ld_rlx64v(ru + 1536);
                return ((or3(or3x(r.m.y, r.m.w, tag), or3x(r.n.y, r.n.w, tag), or3x(r.u0.y, r.u1.y, tag)) | or3x(r.u2.y, r.u3.y, tag)) & 3u) != 0;
            });
            STAMP(b * 16 + 4);
            const float mu = ((F(r.m.x) + F(r.m.z)) + (F(r.n.x) + F(r.n.z))) * (1.0f / DM);
            const float var = fmaxf(((F(r.m.y) + F(r.m.w)) + (F(r.n.y) + F(r.n.w))) * (1.0f / DM) - mu * mu, 0.f);
            const float rs = rsq(fmaf(var + 1e-5f, 1e-5f, var));
            const float x = (((F(r.u0.x) + F(r.u1.x)) + (F(r.u2.x) + F(r.u3.x))) - mu * cs1.x) * rs + F(b1p << 16);
            const float y = (((F(r.u0.y) + F(r.u1.y)) + (F(r.u2.y) + F(r.u3.y))) - mu * cs1.y) * rs + F(b1p & 0xffff0000u);
            constexpr float C0 = -2.0f * 0.7978845608028654f * 1.4426950408889634f;
            sts32(sb + OFF_H + cw * 128 + ln * 4, pack_bf16((x * FIX_SCALE) * rcp(1.0f + ex2(x * fmaf(x * x, 0.044715f * C0, C0))),
                                                           (y * FIX_SCALE) * rcp(1.0f + ex2(y * fmaf(y * y, 0.044715f * C0, C0)))));
            nb_arrive(NB_H + cw);
        }
        STAMP(b * 16 + 5);
        if (layer) {
            FRESH_LANE();
            if (b == NB - 1 && ln == 0) mbar_arrive(barq(sb, BAR_DONE));
            if (b == NB - 1 && h >= 5) { STAMP(b * 16 + 6); break; }
            if (h < 5) {
                const unsigned char* const a = GP(arb + nar + 256 + boff(slot) + voff(h) + (ln >> 3) * 1024 + (ln & 7) * 8);
                __nv_bfloat16* const o = p.out + 160 * j + 32 * h + ln;
                u64 r;
                poll(DELAY_AR2, [&]() { r = ld_rlx64(a); return (((unsigned)r ^ (cbase + CNT2)) & 1023u) != 0; });
                const unsigned ob = bf16_bits(from_fix(r));
                if (b == NB - 1) { o[(NB - 1) * DM] = __ushort_as_bfloat16((unsigned short)ob); STAMP(b * 16 + 6); break; }
                sts16(sb + OFF_Q + b * QSLOT + ln * 2, ob);
                if (b == NB - 2) {
#pragma unroll 1
                    for (int r = 0; r < NB - 1; r++) o[r * DM] = __ushort_as_bfloat16((unsigned short)lds16(sb + OFF_Q + r * QSLOT + ln * 2));
                }
            } else delay(DELAY_AR2 + 600);
            const unsigned char* const a = GP(clo - (ln >> 3) * 4096 + nar + 256 + boff(slot));
            u64 r;
            int it = 0;
            while (true) {
                r = ld_rlx64(a);
                if (__all_sync(0xffffffffu, (((unsigned)r ^ (cbase + CNT2)) & 1023u) == 0)) break;
                if (++it > SPIN_LIMIT) bail();
            }
            if (ln < 5) sts64u(sb + OFF_PREV + (4 + slot) * 64 + ln * 8, r);
            __syncwarp();
            if (b == NB - 3 && ln == 0) mbar_arrive(barq(sb, BAR_L25));
            STAMP(b * 16 + 6);
        } else {
            const unsigned qb = slo + h * 65536;
            {
                FRESH_LANE();
                const unsigned char* const ra = GP(arb + nar + 256 + boff(slot) + (ln >> 3) * 1024 + (ln & 7) * 8);
                unsigned char* const wm = GP(qb + QS_OFF + cw * 32 + j * 8 + ln * 4096);
                u64 r[5];
                float s1, s2;
                delay(mlp ? DELAY_AR2 : DELAY_AR2 + 600);
                const unsigned fence = poll_x(ra, cbase + CNT2, 0, r, sb + OFF_X2 + cw * 320, ln, NB_X2 + cw, s1, s2);
                STAMP(b * 16 + 6);
                if (ln < 2) st_rlx64(wm, __float_as_uint(s1), tagf(s2, tag));
                if (ln == h) {
#pragma unroll
                    for (int v = 0; v < 5; v++) sts64u(sb + OFF_PREV + (4 + slot) * 64 + v * 8, r[v]);
                    sts32(sb + OFF_PREV + (4 + slot) * 64 + 56, fence);
                }
            }
            FRESH_LANE();
            const float4 cs = lds128f(sb + OFF_CSQ + ln * 16);
            Rec4 r;
            delay(DELAY_Q);
            poll4(GP(qb + Q_OFF + (ngr ^ 4096) + cw * 64 + (ln >> 2) * 128 + (ln & 3) * 16), GP(qb + QS_OFF + ngr + cw * 32), tag, 0, r);
            STAMP(b * 16 + 7);
            const float mu = ((F(r.m.x) + F(r.m.z)) + (F(r.n.x) + F(r.n.z))) * (1.0f / DM);
            const float var = fmaxf(((F(r.m.y) + F(r.m.w)) + (F(r.n.y) + F(r.n.w))) * (1.0f / DM) - mu * mu, 0.f);
            store_q(sb, 8 + cw, ln, pksum(r.a0, r.a1, r.a2, r.a3), cs, mu, rsq(var + 1e-5f));
            if (b == NB - 1) nb_arrive(NB_QLAST);
            else { __syncwarp(); if (ln == 0) mbar_arrive(barq(sb, BAR_Q2 + cw)); }
            STAMP(b * 16 + 8);
            if (b == NB - 2) {
                mbar_wait(barq(sb, BAR_L25), 0);
                layer = 1;
            }
        }
    }
    if (cw) {
        if (cw == 1 && h < 20 && lane < 2) st_rlx128(S + FLAG_OFF + j * 1024 + h * 32 + lane * 16, make_uint4(0u, 0u, 0u, 0u));
        if (lane == 0) mbar_arrive(barq(sb, BAR_DONE));
    }
#undef GP
#undef F
#undef U
}

template <int NS>
__device__ __forceinline__ void load_wide(unsigned (&wf)[5][NS][4], uint32_t st, int w, int g, int t) {
    const uint32_t base = st + 8 * t * 320;
#pragma unroll
    for (int s = 0; s < NS; s++)
#pragma unroll
        for (int hf = 0; hf < 2; hf++)
#pragma unroll
            for (int e = 0; e < 2; e++) {
                const uint32_t r = base + (16 * NS * hf + 32 * (s >> 1) + 4 * (s & 1) + 2 * e) * 320;
                const uint2 r0 = lds64(r + 64 * w + 8 * g), r1 = lds64(r + 320 + 64 * w + 8 * g);
                const unsigned s0 = lds16(r + 256 + 16 * w + 2 * g), s1 = lds16(r + 320 + 256 + 16 * w + 2 * g);
                wf[0][s][hf + 2 * e] = lolo(r0.x, r1.x);
                wf[1][s][hf + 2 * e] = hihi(r0.x, r1.x);
                wf[2][s][hf + 2 * e] = lolo(r0.y, r1.y);
                wf[3][s][hf + 2 * e] = hihi(r0.y, r1.y);
                wf[4][s][hf + 2 * e] = lolo(s0, s1);
                asm volatile("" : "+r"(wf[4][s][hf + 2 * e]));
            }
}
template <int NS>
__device__ __forceinline__ void gemv_wide(const unsigned (&wf)[5][NS][4], uint32_t ba, unsigned lo0, unsigned lo1, unsigned hi, int t, float zero) {
    uint4 B[NS / 2];
#pragma unroll
    for (int u = 0; u < NS / 2; u++) B[u] = lds128(ba + 64 * u);
    float acc[5][4];
#pragma unroll
    for (int i = 0; i < 5; i++) { acc[i][0] = acc[i][1] = acc[i][2] = acc[i][3] = 0.f; }
#pragma unroll
    for (int s = 0; s < NS; s++)
#pragma unroll
        for (int i = 0; i < 5; i++)
            mma(acc[i], wf[i][s][0], wf[i][s][1], wf[i][s][2], wf[i][s][3], (s & 1) ? B[s >> 1].z : B[s >> 1].x, (s & 1) ? B[s >> 1].w : B[s >> 1].y);
    const float v0 = fmaf(acc[4][0], zero, acc[0][0]) + acc[0][3], v1 = acc[1][0] + acc[1][3], v2 = acc[2][0] + acc[2][3], v3 = acc[3][0] + acc[3][3];
    const u64 fa = __float2ll_rn((t & 2) ? ((t & 1) ? v3 : v2) : ((t & 1) ? v1 : v0)), fb = __float2ll_rn(acc[4][0] + acc[4][3]);
    unsigned al, bl;
    asm("lop3.b32 %0, %1, 0xfffffc00, %2, 0xea;" : "=r"(al) : "r"((unsigned)fa), "r"(1u));
    asm("lop3.b32 %0, %1, 0xfffffc00, %2, 0xea;" : "=r"(bl) : "r"((unsigned)fb), "r"(1u));
    asm volatile("{\n.reg .pred p;\n.reg .b64 a, b;\nsetp.lt.u32 p, %6, 2;\nmov.b64 a, {%1, %2};\nmov.b64 b, {%4, %5};\n"
                 "red.relaxed.gpu.global.add.u64 [%0], a;\n"
                 "red.relaxed.gpu.global.add.u64 [%0+4096], a;\n"
                 "@p red.relaxed.gpu.global.add.u64 [%3], b;\n}"
                 :: "l"(gptr(lo0, hi)), "r"(al), "r"((unsigned)(fa >> 32)), "l"(gptr(lo1, hi)), "r"(bl), "r"((unsigned)(fb >> 32)), "r"(t) : "memory");
}

#undef PW
#define PW 4
__device__ __forceinline__ void role_g1(const Params& p, uint32_t sb, int w) {
    const int lane = threadIdx.x & 31, g = lane >> 2, t = lane & 3;
    const int cta = blockIdx.x, h = cta >> 2, j = cta & 3;
    const bool mlp = h < NGRP;
    unsigned wf[5][4][4], w1f[10][4];
    {
        mbar_wait(barq(sb, BAR_W + WP_W1), 0); mbar_wait(barq(sb, BAR_W + WP_W1 + 1), 0);
        const uint32_t base1 = sb + ST_W1 + 32 * w + 4 * g;
#pragma unroll
        for (int s = 0; s < 10; s++)
#pragma unroll
            for (int e = 0; e < 2; e++) {
                const uint32_t r = base1 + (krow(s, e) + kstep_t(s) * t) * 128;
                const unsigned r0 = lds32(r), r1 = lds32(r + kpair(s) * 128);
                w1f[s][2 * e] = lolo(r0, r1);
                w1f[s][2 * e + 1] = hihi(r0, r1);
            }
        float a[4] = {0.f, 0.f, 0.f, 0.f};
#pragma unroll
        for (int s = 0; s < 10; s++) mma(a, w1f[s][0], w1f[s][1], w1f[s][2], w1f[s][3], 0x3f803f80u, 0x3f803f80u);
        if (mlp) {
            unsigned char* ua = xbase() + h * 65536 + U_OFF + j * 512 + w * 128 + g * 8 + (t >> 1) * 64 + (t & 1) * 4096;
            st_rlx64(ua, __float_as_uint(a[0]), tagf(a[2], 2u));
            st_rlx64(ua + 16384, __float_as_uint(a[0]), tagf(a[2], 2u));
        }
#pragma unroll 1
        for (int m = WP_WO; m < WP_WO + 4; m++) mbar_wait(barq(sb, BAR_W + m), 0);
        load_wide<4>(wf, sb + ST_WO, w, g, t);
        __syncwarp();
        if (lane == 0) mbar_arrive(barq(sb, BAR_WDONE + 1));
    }
    STAMP(135);
    const unsigned shi = (unsigned)((size_t)xbase() >> 32), slo = (unsigned)(size_t)xbase();
    const unsigned ra0 = slo + AR_OFF + j * 65536 + (lane >> 3) * 1024 + (lane & 7) * 8 + voff(w);
    const unsigned gt = g * 8 + t * 4096;
    const unsigned ra1 = slo + AR_OFF + j * 65536 + w * 1024 + voff(4), ua = slo + h * 65536 + U_OFF + j * 512 + 128 * w;
    const uint32_t ob = sb + OFF_O + (g & 1) * 128 + t * 16, xb = sb + OFF_X1 + t * 16;
#pragma unroll 1
    for (int n = 0; n < 16; n++) {
        int layer, b; item_of(n, layer, b);
        const int slot = layer * 2 + (b & 1), cw = n == 15 ? 0 : layer ? 2 : (b & 1);
        const unsigned tag = ((b >> 1) + 1) & 3;
        nb_sync(NB_O + cw);
        STAMP(n * 8 + 0);
        gemv_wide<4>(wf, ob + cw * 256, ra0 + boff(slot), gt + (ra1 + boff(slot)), shi, t, p.zero);
        STAMP(n * 8 + 1);
        nb_sync(NB_X1 + cw);
        STAMP(n * 8 + 2);
        if (mlp) {
            uint4 B[5];
#pragma unroll
            for (int u = 0; u < 5; u++) B[u] = lds128(xb + cw * 320 + 64 * u);
            float a[4][4];
#pragma unroll
            for (int i = 0; i < 4; i++) { a[i][0] = a[i][1] = a[i][2] = a[i][3] = 0.f; }
#pragma unroll
            for (int s = 0; s < 10; s++)
                mma(a[s & 3], w1f[s][0], w1f[s][1], w1f[s][2], w1f[s][3], (s & 1) ? B[s >> 1].z : B[s >> 1].x, (s & 1) ? B[s >> 1].w : B[s >> 1].y);
            st_rlx64_if(t < 2, gptr(gt + (ua + (b & 1) * 16384 + layer * 64), shi), __float_as_uint((a[2][0] + a[3][0]) + (a[0][0] + a[1][0])), tagf((a[2][2] + a[3][2]) + (a[0][2] + a[1][2]), tag));
        }
        STAMP(n * 8 + 3);
    }
    if (lane == 0) mbar_arrive(barq(sb, BAR_DONE));
}

#undef PW
#define PW 5
__device__ __forceinline__ void role_g2(const Params& p, uint32_t sb, int w) {
    const int lane = threadIdx.x & 31, g = lane >> 2, t = lane & 3;
    const int cta = blockIdx.x, h = cta >> 2, j = cta & 3;
    const bool mlp = h < NGRP;
    unsigned wf[2][10][4], w2f[5][2][4];
    {
        uint4 X[5];
#pragma unroll
        for (int u = 0; u < 4; u++) {
            const __nv_bfloat16* xp = p.x + g * DM + 160 * j + krow(2 * u, 0) + 4 * t;
            const uint2 lo = ldg64(xp), hi = ldg64(xp + 32);
            X[u] = make_uint4(lolo(lo.x, hi.x), hihi(lo.x, hi.x), lolo(lo.y, hi.y), hihi(lo.y, hi.y));
        }
        X[4] = __ldg((const uint4*)(p.x + g * DM + 160 * j + 128 + 8 * t));
#pragma unroll 1
        for (int m = WP_WQ; m < WP_WQ + 4; m++) mbar_wait(barq(sb, BAR_W + m), 0);
        STAMP(130);
        const uint32_t base = sb + ST_WQ + 64 * w + 8 * g;
#pragma unroll
        for (int s = 0; s < 10; s++)
#pragma unroll
            for (int e = 0; e < 2; e++) {
                const uint32_t r = base + (krow(s, e) + kstep_t(s) * t) * 256;
                const uint2 r0 = lds64(r), r1 = lds64(r + kpair(s) * 256);
                wf[0][s][2 * e] = lolo(r0.x, r1.x);
                wf[0][s][2 * e + 1] = hihi(r0.x, r1.x);
                wf[1][s][2 * e] = lolo(r0.y, r1.y);
                wf[1][s][2 * e + 1] = hihi(r0.y, r1.y);
            }
        {
            float a[4] = {0.f, 0.f, 0.f, 0.f}, c[4] = {0.f, 0.f, 0.f, 0.f}, sa[4] = {0.f, 0.f, 0.f, 0.f}, sc[4] = {0.f, 0.f, 0.f, 0.f};
#pragma unroll
            for (int s = 0; s < 10; s++) {
                const unsigned b0 = (s & 1) ? X[s >> 1].z : X[s >> 1].x, b1 = (s & 1) ? X[s >> 1].w : X[s >> 1].y;
                mma(a, wf[0][s][0], wf[0][s][1], wf[0][s][2], wf[0][s][3], b0, b1);
                mma(c, wf[1][s][0], wf[1][s][1], wf[1][s][2], wf[1][s][3], b0, b1);
                mma(sa, wf[0][s][0], wf[0][s][1], wf[0][s][2], wf[0][s][3], 0x3f803f80u, 0x3f803f80u);
                mma(sc, wf[1][s][0], wf[1][s][1], wf[1][s][2], wf[1][s][3], 0x3f803f80u, 0x3f803f80u);
            }
            unsigned char* qm = xbase() + h * 65536 + j * 1024 + (8 * w + g) * 16;
            st_rlx128(qm + (t & 1) * 16384 + (t >> 1) * 4096, pkt(a[0], a[2], c[0], c[2], 2u));
            st_rlx128(qm + (t & 1) * 16384 + (t >> 1) * 4096 + 512, pkt(a[1], a[3], c[1], c[3], 2u));
            st_rlx128(qm + Q_OFF + (t >> 1) * 512 + (t & 1) * 4096, pkt(sa[0], sa[2], sc[0], sc[2], 2u));
        }
        mbar_wait(barq(sb, BAR_W + WP_W2), 0); mbar_wait(barq(sb, BAR_W + WP_W2 + 1), 0);
        load_wide<2>(w2f, sb + ST_W2, w, g, t);
        __syncwarp();
        if (lane == 0) mbar_arrive(barq(sb, BAR_WDONE));
        STAMP(131);
    }
    const unsigned shi = (unsigned)((size_t)xbase() >> 32), slo = (unsigned)(size_t)xbase();
    const unsigned ra0 = slo + AR_OFF + j * 65536 + (lane >> 3) * 1024 + (lane & 7) * 8 + voff(w) + 256;
    const unsigned ra1 = slo + AR_OFF + j * 65536 + w * 1024 + g * 8 + voff(4) + t * 4096 + 256;
    const unsigned qa = slo + h * 65536 + Q_OFF + j * 1024 + (2 * w + (g >> 2)) * 128 + (g & 3) * 16 + t * 4096;
    const uint32_t hb = sb + OFF_H + (g & 1) * 64 + t * 16, xb = sb + OFF_X2 + t * 16;
    STAMP(135);
#pragma unroll 1
    for (int n = 0; n < 16; n++) {
        int layer, b; item_of(n, layer, b);
        const int slot = layer * 2 + (b & 1), cw = n == 15 ? 0 : layer ? 2 : (b & 1);
        if (mlp) {
            nb_sync(NB_H + cw);
            STAMP(n * 8 + 0);
            gemv_wide<2>(w2f, hb + cw * 128, ra0 + boff(slot), ra1 + boff(slot), shi, t, p.zero);
            STAMP(n * 8 + 1);
        }
        if (layer == 0) {
            nb_sync(NB_X2 + cw);
            STAMP(n * 8 + 2);
            float a0[4] = {0.f, 0.f, 0.f, 0.f}, a1[4] = {0.f, 0.f, 0.f, 0.f}, c0[4] = {0.f, 0.f, 0.f, 0.f}, c1[4] = {0.f, 0.f, 0.f, 0.f};
            uint4 B[5];
#pragma unroll
            for (int u = 0; u < 5; u++) B[u] = lds128(xb + cw * 320 + 64 * u);
#pragma unroll
            for (int u = 0; u < 5; u++) {
                mma(a0, wf[0][2 * u][0], wf[0][2 * u][1], wf[0][2 * u][2], wf[0][2 * u][3], B[u].x, B[u].y);
                mma(c0, wf[1][2 * u][0], wf[1][2 * u][1], wf[1][2 * u][2], wf[1][2 * u][3], B[u].x, B[u].y);
                mma(a1, wf[0][2 * u + 1][0], wf[0][2 * u + 1][1], wf[0][2 * u + 1][2], wf[0][2 * u + 1][3], B[u].z, B[u].w);
                mma(c1, wf[1][2 * u + 1][0], wf[1][2 * u + 1][1], wf[1][2 * u + 1][2], wf[1][2 * u + 1][3], B[u].z, B[u].w);
            }
            st_rlx128_if(t < 2, gptr(qa + cw * 64, shi), pkt(a0[0] + a1[0], a0[2] + a1[2], c0[0] + c1[0], c0[2] + c1[2], ((b >> 1) + 1) & 3));
            STAMP(n * 8 + 3);
        }
    }
    if (lane == 0) mbar_arrive(barq(sb, BAR_DONE));
}

#define REG_ATT 128
#define REG_G1 160
#define REG_G2 160
#define REG_AUX 64
template <int N> __device__ __forceinline__ void set_regs() {
    if (N > 128) asm volatile("setmaxnreg.inc.sync.aligned.u32 %0;" :: "n"(N));
    if (N < 128) asm volatile("setmaxnreg.dec.sync.aligned.u32 %0;" :: "n"(N));
}

#define PROF_DUMP() do {} while (0)

__global__ void __launch_bounds__(512, 1) fused_kernel(const __grid_constant__ Params p) {
    extern __shared__ __align__(128) unsigned char smem[];
    const uint32_t sb = (uint32_t)__cvta_generic_to_shared(smem);
    const int cta = blockIdx.x;
    const unsigned t0 = gtime();
    const size_t kvoff = ((size_t)(cta >> 2) * SK + (SK - WIN) + (cta & 3) * 256) * 256;
    const char* kbase = (const char*)p.k + kvoff;
    const int warp = __shfl_sync(0xffffffffu, threadIdx.x >> 5, 0), lane = threadIdx.x & 31;
    if (warp < NFIRST) {
        if (elect_one()) {
            const uint32_t bar = barq(sb, BAR_FULL + warp);
            mbar_init(bar, 1);
            asm volatile("fence.mbarrier_init.release.cluster;" ::: "memory");
            mbar_expect_tx(bar, TILE / 2);
            asm volatile("cp.async.bulk.shared::cluster.global.mbarrier::complete_tx::bytes [%0], [%1], %2, [%3];"
                         :: "r"(sb + warp * (TILE / 2)), "l"(kbase + warp * (TILE / 2)), "r"(TILE / 2), "r"(bar) : "memory");
        }
#undef PW
#define PW 9
        STAMP(0);
    }
    asm volatile("" ::: "memory");
    if (warp >= 4 && warp < 8) {
        if (elect_one()) {
            const uint32_t bar = barq(sb, BAR_W + warp - 4);
            mbar_init(bar, 1);
            asm volatile("fence.mbarrier_init.release.cluster;" ::: "memory");
            mbar_expect_tx(bar, 10240);
            tma2d(sb + ST_WQ + (warp - 4) * 10240, &p.tq, (cta >> 2) * 128, 160 * (cta & 3) + 40 * (warp - 4), bar);
        }
    }
    asm volatile("" ::: "memory");
    if (warp >= 8) {
        if (elect_one()) {
#pragma unroll 1
            for (int bi = warp - 4; bi < NBAR; bi += 8)
                if ((bi & ~3) != BAR_W) mbar_init(barq(sb, bi), (bi == BAR_Q1 || bi >= BAR_WDONE) ? 4 : bi == BAR_DONE ? 15 : bi >= BAR_KXE ? 2 : 1);
            asm volatile("fence.mbarrier_init.release.cluster;" ::: "memory");
            if (warp >= 13) asm volatile("prefetch.tensormap [%0];" :: "l"(&p.tq + (warp - 12)) : "memory");
        }
    }
    __syncthreads();
    if (warp < 4) {
        set_regs<REG_ATT>();
        role_att(p, sb, kbase, warp);
        PROF_DUMP();
    } else if (warp < 8) {
        set_regs<REG_G1>();
        role_g1(p, sb, warp - 4);
        PROF_DUMP();
    } else if (warp < 12) {
        set_regs<REG_G2>();
        role_g2(p, sb, warp - 8);
        PROF_DUMP();
    } else {
        set_regs<REG_AUX>();
        if (warp == 12) role_producer(p, sb, kbase, (const char*)p.v + kvoff, t0);
        else role_chain(p, sb, warp - 13);
        PROF_DUMP();
    }
}

}

typedef CUresult (*EncodeTiledFn)(CUtensorMap*, CUtensorMapDataType, cuuint32_t, void*, const cuuint64_t*, const cuuint64_t*, const cuuint32_t*,
                                  const cuuint32_t*, CUtensorMapInterleave, CUtensorMapSwizzle, CUtensorMapL2promotion, CUtensorMapFloatOOBfill);

static void make_map(EncodeTiledFn enc, CUtensorMap* tm, void* ptr, int cols, int rows, int bcols, int brows, int promo = 0) {
    cuuint64_t gd[2] = {(cuuint64_t)cols, (cuuint64_t)rows}, gs[1] = {(cuuint64_t)cols * 2};
    cuuint32_t bd[2] = {(cuuint32_t)bcols, (cuuint32_t)brows}, es[2] = {1, 1};
    enc(tm, CU_TENSOR_MAP_DATA_TYPE_BFLOAT16, 2, ptr, gd, gs, bd, es, CU_TENSOR_MAP_INTERLEAVE_NONE, CU_TENSOR_MAP_SWIZZLE_NONE,
        (CUtensorMapL2promotion)promo, CU_TENSOR_MAP_FLOAT_OOB_FILL_NONE);
}

extern "C" void kernel_launch(void* const* d_in, const int* in_sizes, int n_in, void* d_out, int out_size) {
    void* fn = nullptr;
    cudaDriverEntryPointQueryResult qr;
    cudaGetDriverEntryPoint("cuTensorMapEncodeTiled", &fn, cudaEnableDefault, &qr);
    Params p;
    make_map((EncodeTiledFn)fn, &p.tq, d_in[3], 4096, DM, 128, 40);
    const int promo = 0;
    make_map((EncodeTiledFn)fn, &p.to, d_in[4], DM, 4096, 160, 32, promo);
    make_map((EncodeTiledFn)fn, &p.t1, d_in[6], FF, DM, 64, 80, promo);
    make_map((EncodeTiledFn)fn, &p.t2, d_in[8], DM, FF, 160, 32, promo);
    p.x = (const __nv_bfloat16*)d_in[0];
    p.k = (const __nv_bfloat16*)d_in[1];
    p.v = (const __nv_bfloat16*)d_in[2];
    p.b1 = (const __nv_bfloat16*)d_in[7];
    p.b2 = (const __nv_bfloat16*)d_in[9];
    p.out = (__nv_bfloat16*)d_out;
    p.zero = 0.f;
    cudaFuncSetAttribute(fused_kernel, cudaFuncAttributeMaxDynamicSharedMemorySize, SMEM_BYTES);
    fused_kernel<<<NCTA, 512, SMEM_BYTES>>>(p);
}
```

```cpp
#include <cuda_runtime.h>
#include <cuda.h>
#include <cuda_bf16.h>
#include <stdint.h>

namespace {

typedef unsigned long long u64;

constexpr int NB = 8, DM = 640, SK = 4096, WIN = 1024, FF = 1728;
constexpr int NCTA = 128, NGRP = 27;
constexpr int TILE = 16384;

constexpr int ST_WQ    = 65536;
constexpr int ST_W2    = ST_WQ + 40960;
constexpr int ST_WO    = 131072;
constexpr int ST_W1    = ST_WO + 40960;
constexpr int OFF_KX   = 196608;
__host__ __device__ constexpr int kx_off(int par) { return par ? OFF_KX : 49152; }
constexpr int OFF_PART = OFF_KX + 16384;
constexpr int OFF_ML   = OFF_PART + 4 * 2048;
constexpr int OFF_O    = OFF_ML + 128;
constexpr int OFF_X1   = OFF_O + 3 * 256;
constexpr int OFF_H    = OFF_X1 + 3 * 320;
constexpr int OFF_X2   = OFF_H + 3 * 128;
constexpr int QSLOT    = 288;
constexpr int OFF_Q    = OFF_X2 + 2 * 320;
constexpr int OFF_P    = OFF_Q + 10 * QSLOT;
constexpr int OFF_CSQ  = OFF_P + 512;
constexpr int OFF_PREV = OFF_CSQ + 512;
constexpr int OFF_CS1  = OFF_PREV + 512;
constexpr int OFF_NEAR = OFF_CS1 + 256;
constexpr int OFF_BAR  = OFF_NEAR + 32;
constexpr int BAR_FULL = 0;
constexpr int BAR_W = 24;
constexpr int BAR_EMPTY = 36;
constexpr int BAR_Q2 = 48;
constexpr int BAR_Q1 = 50;
constexpr int BAR_WDONE = 62;
constexpr int BAR_L25 = 51;
constexpr int BAR_DONE = 52;
constexpr int BAR_NEAR = 53;
constexpr int BAR_KR = 54;
constexpr int BAR_KXE = 58;
constexpr int BAR_ML = 64;
constexpr int NBAR = 68;
constexpr int OFF_PROF = OFF_BAR + NBAR * 8;
constexpr int SMEM_BYTES = OFF_PROF;
constexpr int NB_QLAST = 0, NB_PART = 1, NB_O = 5, NB_X1 = 8, NB_H = 11, NB_X2 = 14;

constexpr unsigned CNT1 = 33, CNT2 = NGRP + 1;
constexpr float FIX_SCALE = 1099511627776.0f;
constexpr int SPIN_LIMIT = 1 << 18;
constexpr int NFIRST = 4;

constexpr int DEPTH = 4;
constexpr int PACE = 327;
constexpr int PACE_OFF = 0, START_T = 2900, PACE_W1 = 345, PACE_W = 410, XFLAGS = 0, RRLEAD = 2;
constexpr int DELAY_AR1 = 500, DELAY_U = 0, DELAY_AR2 = 450, DELAY_Q = 0;

constexpr int U_OFF = 32768, M_OFF = U_OFF + 2048, Q_OFF = 8192, QS_OFF = U_OFF + 2560, AR_OFF = 40960, FLAG_OFF = 524288 + 40960;
__host__ __device__ constexpr int boff(int slot) { return (slot & 1) * 128 + (slot >> 1) * 64; }
__host__ __device__ constexpr int voff(int v) { return (v & 1) * 16384 + ((v >> 1) & 1) * 262144 + (v >> 2) * 1048576; }
__device__ unsigned char g_xchg[4 << 20];

struct Params {
    CUtensorMap tq, to, t1, t2;
    const __nv_bfloat16 *x, *k, *v, *b1, *b2;
    __nv_bfloat16* out;
    float zero;
};

__device__ __forceinline__ unsigned clk() { unsigned c; asm volatile("mov.u32 %0, %%clock;" : "=r"(c)); return c; }
#define STAMP(idx) do {} while (0)
#define STAMPB(idx) do {} while (0)

__device__ __forceinline__ void bail() { asm volatile("exit;"); }
__device__ __forceinline__ void mbar_init(uint32_t bar, uint32_t cnt) { asm volatile("mbarrier.init.shared::cta.b64 [%0], %1;" :: "r"(bar), "r"(cnt) : "memory"); }
__device__ __forceinline__ void mbar_expect_tx(uint32_t bar, uint32_t bytes) { asm volatile("mbarrier.arrive.expect_tx.shared::cta.b64 _, [%0], %1;" :: "r"(bar), "r"(bytes) : "memory"); }
__device__ __forceinline__ void mbar_arrive(uint32_t bar) { asm volatile("mbarrier.arrive.shared::cta.b64 _, [%0];" :: "r"(bar) : "memory"); }
__device__ __forceinline__ void mbar_wait(uint32_t bar, uint32_t parity) {
    int it = 0;
    while (true) {
        uint32_t ok;
        asm volatile("{\n.reg .pred p;\nmbarrier.try_wait.parity.shared::cta.b64 p, [%1], %2;\nselp.u32 %0, 1, 0, p;\n}" : "=r"(ok) : "r"(bar), "r"(parity) : "memory");
        if (ok) break;
        if (++it > SPIN_LIMIT) bail();
    }
}
__device__ __forceinline__ void mbar_wait_or_die(uint32_t bar, uint32_t parity) {
    int it = 0;
    while (true) {
        uint32_t ok;
        asm volatile("{\n.reg .pred p;\nmbarrier.try_wait.parity.shared::cta.b64 p, [%1], %2;\nselp.u32 %0, 1, 0, p;\n}" : "=r"(ok) : "r"(bar), "r"(parity) : "memory");
        if (ok) break;
        if (++it > SPIN_LIMIT) __trap();
    }
}
__device__ __forceinline__ void bulk_load(uint32_t dst, const void* src, uint32_t bytes, uint32_t bar, u64 pol) {
    asm volatile("cp.async.bulk.shared::cluster.global.mbarrier::complete_tx::bytes.L2::cache_hint [%0], [%1], %2, [%3], %4;"
                 :: "r"(dst), "l"(src), "r"(bytes), "r"(bar), "l"(pol) : "memory");
}
__device__ __forceinline__ void nb_sync(int id) { asm volatile("bar.sync %0, 160;" :: "r"(id) : "memory"); }
__device__ __forceinline__ void nb_arrive(int id) { asm volatile("bar.arrive %0, 160;" :: "r"(id) : "memory"); }
__device__ __forceinline__ void delay(unsigned n) { if (n) { unsigned c = clk(); while (clk() - c < n) {} } }

__device__ __forceinline__ uint4 lds128(uint32_t a) { uint4 v; asm volatile("ld.shared.v4.u32 {%0,%1,%2,%3}, [%4];" : "=r"(v.x), "=r"(v.y), "=r"(v.z), "=r"(v.w) : "r"(a)); return v; }
__device__ __forceinline__ uint4 ldsm4(uint32_t a) { uint4 v; asm volatile("ldmatrix.sync.aligned.m8n8.x4.shared.b16 {%0,%1,%2,%3}, [%4];" : "=r"(v.x), "=r"(v.y), "=r"(v.z), "=r"(v.w) : "r"(a)); return v; }
__device__ __forceinline__ uint2 lds64(uint32_t a) { uint2 v; asm volatile("ld.shared.v2.u32 {%0,%1}, [%2];" : "=r"(v.x), "=r"(v.y) : "r"(a)); return v; }
__device__ __forceinline__ float4 lds128f(uint32_t a) { float4 v; asm volatile("ld.shared.v4.f32 {%0,%1,%2,%3}, [%4];" : "=f"(v.x), "=f"(v.y), "=f"(v.z), "=f"(v.w) : "r"(a)); return v; }
__device__ __forceinline__ float2 lds64f(uint32_t a) { float2 v; asm volatile("ld.shared.v2.f32 {%0,%1}, [%2];" : "=f"(v.x), "=f"(v.y) : "r"(a)); return v; }
__device__ __forceinline__ unsigned lds32(uint32_t a) { unsigned v; asm volatile("ld.shared.u32 %0, [%1];" : "=r"(v) : "r"(a)); return v; }
__device__ __forceinline__ u64 lds64u(uint32_t a) { u64 v; asm volatile("ld.shared.u64 %0, [%1];" : "=l"(v) : "r"(a)); return v; }
__device__ __forceinline__ unsigned lds16(uint32_t a) { unsigned short v; asm volatile("ld.shared.u16 %0, [%1];" : "=h"(v) : "r"(a)); return v; }
__device__ __forceinline__ void sts128f(uint32_t a, float x, float y, float z, float w) { asm volatile("st.shared.v4.f32 [%0], {%1,%2,%3,%4};" :: "r"(a), "f"(x), "f"(y), "f"(z), "f"(w) : "memory"); }
__device__ __forceinline__ void sts64f(uint32_t a, float x, float y) { asm volatile("st.shared.v2.f32 [%0], {%1,%2};" :: "r"(a), "f"(x), "f"(y) : "memory"); }
__device__ __forceinline__ void sts64u(uint32_t a, u64 v) { asm volatile("st.shared.u64 [%0], %1;" :: "r"(a), "l"(v) : "memory"); }
__device__ __forceinline__ void sts32(uint32_t a, unsigned v) { asm volatile("st.shared.u32 [%0], %1;" :: "r"(a), "r"(v) : "memory"); }
__device__ __forceinline__ void sts16(uint32_t a, unsigned v) { asm volatile("st.shared.u16 [%0], %1;" :: "r"(a), "h"((unsigned short)v) : "memory"); }

__device__ __forceinline__ uint4 ld_rlx128(const void* p) { uint4 v; asm volatile("ld.relaxed.gpu.global.v4.u32 {%0,%1,%2,%3}, [%4];" : "=r"(v.x), "=r"(v.y), "=r"(v.z), "=r"(v.w) : "l"(p) : "memory"); return v; }
__device__ __forceinline__ void st_rlx128(void* p, uint4 v) { asm volatile("st.relaxed.gpu.global.v4.u32 [%0], {%1,%2,%3,%4};" :: "l"(p), "r"(v.x), "r"(v.y), "r"(v.z), "r"(v.w) : "memory"); }
__device__ __forceinline__ u64 ld_rlx64(const void* p) { u64 v; asm volatile("ld.relaxed.gpu.global.u64 %0, [%1];" : "=l"(v) : "l"(p) : "memory"); return v; }
__device__ __forceinline__ void red64(void* p, u64 v) { asm volatile("red.relaxed.gpu.global.add.u64 [%0], %1;" :: "l"(p), "l"(v) : "memory"); }

__device__ __forceinline__ uint4 ldg128_stream(const void* p, u64 pol) { uint4 v; asm volatile("ld.global.nc.L1::no_allocate.L2::cache_hint.v4.u32 {%0,%1,%2,%3}, [%4], %5;" : "=r"(v.x), "=r"(v.y), "=r"(v.z), "=r"(v.w) : "l"(p), "l"(pol)); return v; }
__device__ __forceinline__ uint2 ldg64(const void* p) { uint2 v; asm volatile("ld.global.nc.L1::no_allocate.v2.u32 {%0,%1}, [%2];" : "=r"(v.x), "=r"(v.y) : "l"(p)); return v; }
__device__ __forceinline__ unsigned ldg32(const void* p) { unsigned v; asm volatile("ld.global.nc.L1::no_allocate.u32 %0, [%1];" : "=r"(v) : "l"(p)); return v; }
__device__ __forceinline__ unsigned ldg16(const void* p) { unsigned short v; asm volatile("ld.global.nc.u16 %0, [%1];" : "=h"(v) : "l"(p)); return v; }

__device__ __forceinline__ void mma(float (&c)[4], unsigned a0, unsigned a1, unsigned a2, unsigned a3, unsigned b0, unsigned b1) {
    asm volatile("mma.sync.aligned.m16n8k16.row.col.f32.bf16.bf16.f32 {%0,%1,%2,%3}, {%4,%5,%6,%7}, {%8,%9}, {%0,%1,%2,%3};"
                 : "+f"(c[0]), "+f"(c[1]), "+f"(c[2]), "+f"(c[3]) : "r"(a0), "r"(a1), "r"(a2), "r"(a3), "r"(b0), "r"(b1));
}
__device__ __forceinline__ unsigned lolo(unsigned a, unsigned b) { return __byte_perm(a, b, 0x5410); }
__device__ __forceinline__ unsigned hihi(unsigned a, unsigned b) { return __byte_perm(a, b, 0x7632); }
__device__ __forceinline__ unsigned bf16_bits(float x) { return __bfloat16_as_ushort(__float2bfloat16_rn(x)); }
__device__ __forceinline__ float bf16_val(unsigned b) { return __uint_as_float(b << 16); }
__device__ __forceinline__ float bf16_round(float x) { return bf16_val(bf16_bits(x)); }
__device__ __forceinline__ unsigned pack_bf16(float lo, float hi) { unsigned r; asm("cvt.rn.bf16x2.f32 %0, %1, %2;" : "=r"(r) : "f"(hi), "f"(lo)); return r; }
__device__ __forceinline__ float ex2(float x) { float r; asm("ex2.approx.ftz.f32 %0, %1;" : "=f"(r) : "f"(x)); return r; }
__device__ __forceinline__ u64 to_fix_scaled(float vs) { return ((u64)__float2ll_rn(vs) & ~1023ull) | 1ull; }
__device__ __forceinline__ u64 to_fix(float v) { return to_fix_scaled(v * FIX_SCALE); }
__device__ __forceinline__ float from_fix(u64 w) {
    return fmaf(__uint2float_rn((unsigned)w & ~1023u), 1.0f / FIX_SCALE, __int2float_rn((int)(w >> 32)) * (1.0f / 256.0f));
}
__device__ __forceinline__ uint2 ld_rlx64v(const void* p) { const u64 v = ld_rlx64(p); return make_uint2((unsigned)v, (unsigned)(v >> 32)); }
__device__ __forceinline__ void st_rlx64(void* p, unsigned x, unsigned y) { asm volatile("st.relaxed.gpu.global.u64 [%0], %1;" :: "l"(p), "l"((u64)x | ((u64)y << 32)) : "memory"); }
__device__ __forceinline__ void st_rlx64_if(bool c, void* p, unsigned x, unsigned y) {
    asm volatile("{\n.reg .pred p;\nsetp.ne.u32 p, %3, 0;\n@p st.relaxed.gpu.global.v2.u32 [%0], {%1, %2};\n}" :: "l"(p), "r"(x), "r"(y), "r"((unsigned)c) : "memory");
}
__device__ __forceinline__ void st_rlx128_if(bool c, void* p, uint4 v) {
    asm volatile("{\n.reg .pred p;\nsetp.ne.u32 p, %5, 0;\n@p st.relaxed.gpu.global.v4.u32 [%0], {%1, %2, %3, %4};\n}"
                 :: "l"(p), "r"(v.x), "r"(v.y), "r"(v.z), "r"(v.w), "r"((unsigned)c) : "memory");
}
__device__ __forceinline__ unsigned char* xbase() { return (unsigned char*)(((size_t)g_xchg + 0x1fffff) & ~(size_t)0x1fffff); }

__device__ __forceinline__ uint32_t barq(uint32_t sb, int i) { return sb + OFF_BAR + i * 8; }
__device__ __forceinline__ float4 sum4(float4 a, float4 b, float4 c, float4 d) {
    return make_float4((a.x + b.x) + (c.x + d.x), (a.y + b.y) + (c.y + d.y), (a.z + b.z) + (c.z + d.z), (a.w + b.w) + (c.w + d.w));
}

__device__ __forceinline__ void item_of(int n, int& layer, int& b) {
    if (n == 0) { layer = 0; b = 0; }
    else if (n == 15) { layer = 1; b = 7; }
    else if (n & 1) { layer = 0; b = (n + 1) >> 1; }
    else { layer = 1; b = (n >> 1) - 1; }
}

constexpr size_t BSTRIDE = (size_t)32 * SK * 256;

__device__ __forceinline__ void tma2d(uint32_t dst, const CUtensorMap* tm, int c0, int c1, uint32_t bar) {
    u64 pol;
    asm("createpolicy.fractional.L2::evict_first.b64 %0, 1.0;" : "=l"(pol));
    asm volatile("cp.async.bulk.tensor.2d.shared::cluster.global.mbarrier::complete_tx::bytes.L2::cache_hint [%0], [%1, {%3, %4}], [%2], %5;"
                 :: "r"(dst), "l"(tm), "r"(bar), "r"(c0), "r"(c1), "l"(pol) : "memory");
}
constexpr int WP_WQ = 0, WP_W2 = 4, WP_W1 = 6, WP_WO = 8;
__device__ __forceinline__ void issue_weights(const Params& p, uint32_t sb, int m) {
    const int cta = blockIdx.x, h = cta >> 2, j = cta & 3;
    const uint32_t bar = barq(sb, BAR_W + m);
    if (m < WP_W1) tma2d(sb + ST_W2 + (m - WP_W2) * 10240, &p.t2, 160 * j, 64 * h + 32 * (m - WP_W2), bar);
    else if (m < WP_WO) tma2d(sb + ST_W1 + (m - WP_W1) * 10240, &p.t1, 64 * h, 160 * j + 80 * (m - WP_W1), bar);
    else tma2d(sb + ST_WO + (m - WP_WO) * 10240, &p.to, 160 * j, 128 * h + 32 * (m - WP_WO), bar);
}
__device__ __forceinline__ unsigned gtime() { unsigned t; asm volatile("mov.u32 %0, %%globaltimer_lo;" : "=r"(t)); return t; }
#define PW 9
__device__ __forceinline__ bool elect_one() { unsigned r; asm volatile("{\n.reg .pred p;\nelect.sync _|p, 0xffffffff;\nselp.u32 %0, 1, 0, p;\n}" : "=r"(r)); return r; }
__device__ __forceinline__ void issue_reread(const Params& p, uint32_t sb, const char* kbase, int b, int w, int part, u64 pol) {
    const uint32_t bar = barq(sb, BAR_KR + w);
    if (XFLAGS & 2) { if (part == 0 && elect_one()) mbar_arrive(bar); return; }
    if (elect_one()) {
        if (part == 0) mbar_expect_tx(bar, 12288);
        bulk_load(sb + w * 12288 + part * 4096, kbase + b * BSTRIDE + w * 12288 + part * 4096, 4096, bar, pol);
    }
}
__device__ __forceinline__ void role_producer(const Params& p, uint32_t sb, const char* kbase, const char* vbase, unsigned t0) {
    u64 pol_first, pol_norm;
    asm volatile("createpolicy.fractional.L2::evict_first.b64 %0, 1.0;" : "=l"(pol_first));
    asm volatile("createpolicy.fractional.L2::evict_normal.b64 %0, 1.0;" : "=l"(pol_norm));
    STAMP(1);
    auto until = [&](unsigned t) { int it = 0; while ((int)(gtime() - t) < 0 && ++it < 4096) {} };
    const bool mlp = (blockIdx.x >> 2) < NGRP;
    {
        const int lane = threadIdx.x & 31;
        if (lane < 8) { if (lane < 4 && !mlp) mbar_arrive(barq(sb, BAR_W + 4 + lane)); else mbar_expect_tx(barq(sb, BAR_W + 4 + lane), 10240); }
        else if (lane < 8 + 16 - NFIRST) mbar_expect_tx(barq(sb, BAR_FULL + NFIRST + lane - 8), TILE / 2);
        __syncwarp();
    }
    unsigned tnext = t0 + START_T + (((blockIdx.x * 37) & 127) * PACE >> 7);
#pragma unroll 1
    for (int m = 4; m < 12; m++) {
        until(tnext);
        if ((m >= WP_WO || mlp) && elect_one()) issue_weights(p, sb, m);
        tnext += m < WP_WO ? PACE_W1 : PACE_W;
        STAMP(136 + 1 + 2 * m);
    }
    uint32_t pbar = barq(sb, BAR_FULL + 16 - DEPTH), ppar = 0;
    int pleft = DEPTH, pgrp = 1;
    auto gate = [&](uint32_t bar, bool steady) {
        if (steady && elect_one()) mbar_expect_tx(bar, TILE / 2);
        until(tnext);
        if (steady) mbar_wait_or_die(pbar, ppar);
    };
    auto advance = [&](bool steady) {
        tnext += PACE;
        if (steady) {
            pbar += 8;
            if (--pleft == 0) {
                pgrp++;
                pleft = 8;
                const int pb = pgrp >> 1;
                pbar = barq(sb, BAR_FULL + ((pgrp & 1) ? 8 + (pb & 1) * 8 : 0));
                ppar = ((pgrp & 1) ? pb >> 1 : pb) & 1;
            }
        }
    };
#pragma unroll 1
    for (int b = 0; b < NB; b++) {
        const char* ks = kbase + b * BSTRIDE;
        const char* vs = vbase + b * BSTRIDE;
        const int par = b & 1, epar = ((b >> 1) & 1) ^ 1;
        if (b == 1) tnext += PACE_OFF;
#pragma unroll 1
        for (int i = b ? 0 : NFIRST; i < 8; i++) {
            if (b) {
                if (i >= 6) mbar_wait_or_die(barq(sb, BAR_KXE + par * 2 + i - 6), epar);
                else if (i != 2 && i != 5) mbar_wait_or_die(barq(sb, BAR_EMPTY + (i > 2 ? i - 1 : i)), par ^ 1);
            }
            if (!(i & 1)) STAMP(136 + b * 16 + i);
            const uint32_t bar = barq(sb, BAR_FULL + i), dst = sb + i * 8192 + (i >= 6 && par ? OFF_KX - 49152 : 0);
            const u64 pol = (i >= 6 || (XFLAGS & 8)) ? pol_first : pol_norm;
            gate(bar, b);
            if (elect_one()) bulk_load(dst, ks + i * 8192, 8192, bar, pol);
            STAMP(b * 16 + i);
            advance(b);
        }
        if (b < 2) mbar_wait_or_die(barq(sb, BAR_WDONE + b), 0);
#pragma unroll 1
        for (int w = 0; w < 4; w++) {
            const uint32_t bar = barq(sb, BAR_FULL + 8 + par * 8 + 2 * w), dst = sb + (4 + par * 4 + w) * TILE;
            if (b) mbar_wait_or_die(barq(sb, BAR_EMPTY + 4 + par * 4 + w), epar);
            STAMP(136 + b * 16 + 8 + 2 * w);
            gate(bar, b);
            if (elect_one()) bulk_load(dst, vs + w * 12288, 8192, bar, pol_first);
            STAMP(b * 16 + 8 + 2 * w);
            advance(b);
            gate(bar + 8, b);
            if (elect_one()) {
                bulk_load(dst + 8192, vs + w * 12288 + 8192, 4096, bar + 8, pol_first);
                bulk_load(dst + 12288, vs + 49152 + w * 4096, 4096, bar + 8, pol_first);
            }
            STAMP(b * 16 + 9 + 2 * w);
            advance(b);
        }
    }
    mbar_wait_or_die(barq(sb, BAR_DONE), 0);
}

__device__ __forceinline__ unsigned tagf(float x, unsigned tag) { unsigned r; asm("lop3.b32 %0, %1, 0xfffffffc, %2, 0xea;" : "=r"(r) : "r"(__float_as_uint(x)), "r"(tag)); return r; }
__device__ __forceinline__ uint4 pkt(float x, float y, float z, float w, unsigned tag) {
    return make_uint4(__float_as_uint(x), __float_as_uint(y), __float_as_uint(z), tagf(w, tag));
}
__device__ __forceinline__ float4 pksum(const uint4& a, const uint4& b, const uint4& c, const uint4& d) {
    return make_float4((__uint_as_float(a.x) + __uint_as_float(b.x)) + (__uint_as_float(c.x) + __uint_as_float(d.x)),
                       (__uint_as_float(a.y) + __uint_as_float(b.y)) + (__uint_as_float(c.y) + __uint_as_float(d.y)),
                       (__uint_as_float(a.z) + __uint_as_float(b.z)) + (__uint_as_float(c.z) + __uint_as_float(d.z)),
                       (__uint_as_float(a.w) + __uint_as_float(b.w)) + (__uint_as_float(c.w) + __uint_as_float(d.w)));
}
__device__ __forceinline__ float rsq(float x) { float r; asm("rsqrt.approx.ftz.f32 %0, %1;" : "=f"(r) : "f"(x)); return r; }
__device__ __forceinline__ float rcp(float x) { float r; asm("rcp.approx.ftz.f32 %0, %1;" : "=f"(r) : "f"(x)); return r; }
__device__ __forceinline__ void store_q(uint32_t sb, int qslot, int lane, float4 u, float4 cs, float mu, float rs) {
    const uint32_t qa = sb + OFF_Q + qslot * QSLOT + ((lane >> 1) & 3) * 32 + (lane >> 3) * 8 + (lane & 1) * 4;
    sts32(qa, pack_bf16((u.x - mu * cs.x) * rs, (u.y - mu * cs.y) * rs));
    sts32(qa + 144, pack_bf16((u.z - mu * cs.z) * rs, (u.w - mu * cs.w) * rs));
}

struct AttCtx {
    uint32_t sb;
    int w, lane, g, t;
    unsigned sel0, sel1;
    uint32_t pst, qoff;
};

#define SCHED_FENCE(i) fv[i] = clk()
template <class G0, class G1>
__device__ __forceinline__ void softmax_part(const AttCtx& c, const float (&v)[8], float& m_out, unsigned& pp_out, G0 gap0, G1 gap1) {
    const bool ph = (c.t ^ c.g) & 1, hi = c.t >> 1;
    float u0 = ph ? v[1] : v[0], u1 = ph ? v[3] : v[2], u2 = ph ? v[5] : v[4], u3 = ph ? v[7] : v[6];
    const float sc = 0.08838834764831845f * 1.4426950408889634f;
    float s0 = (hi ? u2 : u0) * sc, s1 = (hi ? u3 : u1) * sc;
    float mx = fmaxf(s0, s1);
    int mi = __float_as_int(mx); mi ^= (mi >> 31) & 0x7fffffff;
    gap0();
    mi = __reduce_max_sync(0xffffffffu, mi);
    mi ^= (mi >> 31) & 0x7fffffff;
    const float m = __int_as_float(mi);
    const float e0 = ex2(s0 - m), e1 = ex2(s1 - m);
    gap1();
    const unsigned pp = pack_bf16(e0, e1);
    sts16(c.pst, pp & 0xffffu);
    sts16(c.pst + 32, pp >> 16);
    m_out = m; pp_out = pp;
    __syncwarp();
}
__device__ __forceinline__ unsigned sum_p(unsigned pp) {
    return __reduce_add_sync(0xffffffffu, __float2uint_rn((__uint_as_float(pp << 16) + __uint_as_float(pp & 0xffff0000u)) * 16777216.0f));
}
__device__ __forceinline__ void publish_ml(const AttCtx& c, int slot, float m, unsigned li) {
    if (c.lane == 0) { sts64f(c.sb + OFF_ML + slot * 32 + c.w * 8, m, __uint_as_float(li)); mbar_arrive(barq(c.sb, BAR_ML + slot)); }
}

__device__ __forceinline__ void load_q(const AttCtx& c, int qslot, uint2 (&qf)[4]) {
    const uint32_t qa = c.qoff + qslot * QSLOT;
#pragma unroll
    for (int j = 0; j < 4; j++) qf[j] = lds64((j & 1 ? qa ^ 8 : qa) + (j >> 1) * 16);
}

template <int NT>
__device__ __forceinline__ void qk_tiles(const uint4 (*kr)[4], const uint2 (&qf)[4], float* v) {
    float acc[NT][4];
#pragma unroll
    for (int mt = 0; mt < NT; mt++) { acc[mt][0] = acc[mt][1] = acc[mt][2] = acc[mt][3] = 0.f; }
#pragma unroll
    for (int j = 0; j < 4; j++)
#pragma unroll
        for (int mt = 0; mt < NT; mt++) mma(acc[mt], kr[mt][j].x, kr[mt][j].y, kr[mt][j].z, kr[mt][j].w, qf[j].x, qf[j].y);
#pragma unroll
    for (int mt = 0; mt < NT; mt++) v[mt] = acc[mt][0] + acc[mt][3];
}
template <int NT>
__device__ __forceinline__ void k_from_smem(uint4 (*kr)[4], uint32_t aE, uint32_t aO) {
#pragma unroll
    for (int j = 0; j < 4; j++)
#pragma unroll
        for (int mt = 0; mt < NT; mt++) kr[mt][j] = lds128((((j ^ mt) & 1) ? aO : aE) + mt * 2048 + (j >> 1) * 128);
}

template <int I0, int I1>
__device__ __forceinline__ void v_load(uint4 (&vr)[16], uint32_t va) {
#pragma unroll
    for (int i = I0; i < I1; i++) vr[i] = ldsm4(va + i * 512);
}
template <int I0, int I1>
__device__ __forceinline__ void pv_regs(const AttCtx& c, float (&o)[4][4], const uint4 (&vr)[16], const uint4* pw) {
#pragma unroll
    for (int i = I0; i < I1; i++) {
        const unsigned pv[4] = {pw[i].x, pw[i].y, pw[i].z, pw[i].w};
#pragma unroll
        for (int k = 0; k < 4; k++)
            mma(o[k], vr[i * 4 + k].x, vr[i * 4 + k].y, vr[i * 4 + k].z, vr[i * 4 + k].w, __byte_perm(pv[k], 0, c.sel0), __byte_perm(pv[k], 0, c.sel1));
    }
}
__device__ __forceinline__ void publish_part(const AttCtx& c, const float (&o)[4][4], int slot) {
    sts128f(c.sb + OFF_PART + slot * 2048 + c.w * 512 + c.lane * 16,
            (o[0][0] + o[1][0]) + (o[2][0] + o[3][0]), (o[0][1] + o[1][1]) + (o[2][1] + o[3][1]),
            (o[0][2] + o[1][2]) + (o[2][2] + o[3][2]), (o[0][3] + o[1][3]) + (o[2][3] + o[3][3]));
    nb_arrive(NB_PART + slot);
}

#undef PW
#define PW w
__device__ __forceinline__ void role_att(const Params& p, uint32_t sb, const char* kbase, int w) {
    u64 pol_first;
    asm volatile("createpolicy.fractional.L2::evict_first.b64 %0, 1.0;" : "=l"(pol_first));
    AttCtx c;
    c.sb = sb; c.w = w; c.lane = threadIdx.x & 31; c.g = c.lane >> 2; c.t = c.lane & 3;
    const bool act = (c.g >> 1) == c.t;
    c.sel0 = act ? ((c.g & 1) ? 0x1044u : 0x4410u) : 0x4444u;
    c.sel1 = act ? ((c.g & 1) ? 0x3244u : 0x4432u) : 0x4444u;
    c.pst = sb + OFF_P + c.w * 128 + ((((c.t ^ c.g) & 1) + 4 * (c.t >> 1)) * 8 + c.g) * 2;
    c.qoff = sb + OFF_Q + (c.g & 1) * 144 + c.t * 32 + ((c.g >> 1) & 1) * 8;
    asm volatile("" : "+r"(c.pst), "+r"(c.qoff), "+r"(c.sel0), "+r"(c.sel1));
    const uint32_t offE = c.g * 256 + c.t * 16 + 64 * (c.g & 1);
    const uint32_t kE = sb + c.w * 12288 + offE, kO = kE ^ 64;
    const uint32_t xE0 = sb + c.w * 4096 + offE;
    const uint32_t pa = sb + OFF_P + c.w * 128;
    const uint32_t barkr = barq(sb, BAR_KR + c.w);
    {
        const int lane = c.lane;
        float mu0, rs0;
        {
            float s1 = 0.f, s2 = 0.f;
#pragma unroll
            for (int u = 0; u < 5; u++) {
                const uint4 y = __ldg((const uint4*)(p.x + (2 * w + (lane >> 4)) * DM + 128 * u + 8 * (lane & 15)));
                const unsigned yy[4] = {y.x, y.y, y.z, y.w};
#pragma unroll
                for (int i = 0; i < 4; i++) {
                    const float x0 = __uint_as_float(yy[i] << 16), x1 = __uint_as_float(yy[i] & 0xffff0000u);
                    s1 += x0 + x1; s2 += fmaf(x0, x0, x1 * x1);
                }
            }
#pragma unroll
            for (int o = 8; o; o >>= 1) { s1 += __shfl_xor_sync(0xffffffffu, s1, o); s2 += __shfl_xor_sync(0xffffffffu, s2, o); }
            mu0 = s1 * (1.0f / DM);
            rs0 = rsq(fmaxf(s2 * (1.0f / DM) - mu0 * mu0, 0.f) + 1e-5f);
        }
        STAMP(128);
        mbar_wait(barq(sb, BAR_WDONE), 0);
        STAMP(129);
        const unsigned char* a = xbase() + (blockIdx.x >> 2) * 65536 + lane * 16;
        const unsigned char* a1 = a + (w & 1) * 16384 + (w >> 1) * 4096;
        uint4 r[3][4];
        int it = 0;
        while (true) {
            unsigned d = 0;
#pragma unroll
            for (int i = 0; i < 4; i++) { r[0][i] = ld_rlx128(a + Q_OFF + i * 1024); r[1][i] = ld_rlx128(a1 + i * 1024); r[2][i] = ld_rlx128(a1 + 512 + i * 1024); }
#pragma unroll
            for (int i = 0; i < 4; i++) d |= (r[0][i].w ^ 2u) | (r[1][i].w ^ 2u) | (r[2][i].w ^ 2u);
            if (__all_sync(0xffffffffu, (d & 3u) == 0)) break;
            if (++it > SPIN_LIMIT) bail();
        }
        const float4 cs = pksum(r[0][0], r[0][1], r[0][2], r[0][3]);
        if (w == 0) sts128f(sb + OFF_CSQ + lane * 16, cs.x, cs.y, cs.z, cs.w);
#pragma unroll
        for (int k = 0; k < 2; k++)
            store_q(sb, 2 * w + k, lane, pksum(r[1 + k][0], r[1 + k][1], r[1 + k][2], r[1 + k][3]), cs, __shfl_sync(0xffffffffu, mu0, k * 16), __shfl_sync(0xffffffffu, rs0, k * 16));
        __syncwarp();
        if (lane == 0) mbar_arrive(barq(sb, BAR_Q1));
        STAMP(130);
    }
    mbar_wait(barq(sb, BAR_Q1), 0);
    unsigned fz = 0;

#pragma unroll 1
    for (int b = 0; b <= NB; b++) {
        uint2 qf[4];
        float v[8], o[4][4], m;
        unsigned pp;
        if (b < NB) {
            load_q(c, b, qf);
            {
                const int p0 = c.w + (c.w >> 1);
                mbar_wait(barq(sb, BAR_FULL + p0), b & 1);
                mbar_wait(barq(sb, BAR_FULL + p0 + 1), b & 1);
                uint4 kr[6][4];
                k_from_smem<6>(kr, kE, kO);
                qk_tiles<6>(kr, qf, v);
            }
            __syncwarp();
            if (b == 0 && c.lane == 0) mbar_arrive(barq(sb, BAR_EMPTY + c.w));
            auto reread = [&]() {
#pragma unroll 1
                for (int part = 0; part < 3; part++) {
                    const int pos = 3 * c.w + part + RRLEAD;
                    if (pos >= 8) mbar_wait(barq(sb, BAR_FULL + (b & 1) * 8 + pos), (b >> 1) & 1);
                    else mbar_wait(barq(sb, BAR_FULL + pos), b & 1);
                    issue_reread(p, sb, kbase, b - 1, c.w, part, pol_first);
                }
            };
            if (b && c.w < 2) reread();
            {
                mbar_wait(barq(sb, BAR_FULL + 6 + (c.w >> 1)), b & 1);
                uint4 kr[2][4];
                k_from_smem<2>(kr, xE0 + kx_off(b & 1), (xE0 + kx_off(b & 1)) ^ 64);
                qk_tiles<2>(kr, qf, v + 6);
            }
            STAMP(b * 16 + 0);
            softmax_part(c, v, m, pp, []() {}, []() {});
            publish_ml(c, b & 1, m, sum_p(pp));
            if (b && c.w >= 2) reread();
        }
        if (b < NB) {
            STAMP(b * 16 + 1);
            const int vs = 4 + (b & 1) * 4 + c.w;
#pragma unroll
            for (int i = 0; i < 4; i++) { o[i][0] = o[i][1] = o[i][2] = o[i][3] = 0.f; }
#pragma unroll 1
            for (int hh = 0; hh < 2; hh++) {
                uint2 pb[16];
#pragma unroll
                for (int i = 0; i < 4; i++) {
                    const uint4 pw = lds128(pa + hh * 64 + i * 16);
                    const unsigned pv[4] = {pw.x, pw.y, pw.z, pw.w};
#pragma unroll
                    for (int k = 0; k < 4; k++) {
                        pb[i * 4 + k] = make_uint2(__byte_perm(pv[k], 0, c.sel0), __byte_perm(pv[k], 0, c.sel1));
                        asm volatile("" : "+r"(pb[i * 4 + k].x), "+r"(pb[i * 4 + k].y));
                    }
                }
                const uint32_t va = sb + vs * TILE + hh * 8192 + c.lane * 16;
                mbar_wait(barq(sb, BAR_FULL + vs * 2 + hh), (b >> 1) & 1);
                STAMP(b * 16 + 2);
                uint4 vr[16];
                v_load<0, 16>(vr, va);
#pragma unroll
                for (int i = 0; i < 16; i++) mma(o[i & 3], vr[i].x, vr[i].y, vr[i].z, vr[i].w, pb[i].x, pb[i].y);
            }
            publish_part(c, o, b & 1);
            STAMP(b * 16 + 3);
        }
        if (b > 0) {
            const int b2 = b - 1;
            const int vs = 4 + (b2 & 1) * 4 + c.w;
            const uint32_t va = sb + vs * TILE + c.lane * 16;
            const uint32_t xE = xE0 + kx_off(b2 & 1), xO = xE ^ 64;
            uint4 kr[6][4];
            mbar_wait(barkr, b2 & 1);
            k_from_smem<6>(kr, kE, kO);
            asm volatile("" :: "r"(kr[5][3].x), "r"(kr[4][3].x), "r"(kr[3][3].x), "r"(kr[2][3].x), "r"(kr[1][3].x), "r"(kr[0][3].x) : "memory");
            __syncwarp();
            if (c.lane == 0) mbar_arrive(barq(sb, BAR_EMPTY + c.w));
            if (b == NB - 1) {
#pragma unroll 1
                for (int part = 0; part < 3; part++) issue_reread(p, sb, kbase, NB - 1, c.w, part, pol_first);
            }
            STAMP(b2 * 16 + 4);
            if (b == NB) { nb_sync(NB_QLAST); if (c.lane == 0) mbar_arrive(barq(sb, BAR_DONE)); }
            else mbar_wait(barq(sb, BAR_Q2 + (b2 & 1)), (b2 >> 1) & 1);
            STAMPB(b2 * 16 + 5);
            load_q(c, 8 + (b2 & 1), qf);
            uint4 kx[2][4], vr[16];
            float acc[4][4];
            unsigned fv[15];
#pragma unroll
            for (int jj = 0; jj < 4; jj++) {
#pragma unroll
                for (int mt = 0; mt < 4; mt++) {
                    if (jj == 0) { acc[mt][0] = acc[mt][1] = acc[mt][2] = acc[mt][3] = 0.f; }
                    mma(acc[mt], kr[mt][jj].x, kr[mt][jj].y, kr[mt][jj].z, kr[mt][jj].w, qf[jj].x, qf[jj].y);
                }
                kx[0][jj] = lds128(((jj & 1) ? xO : xE) + (jj >> 1) * 128);
                kx[1][jj] = lds128(((jj & 1) ? xE : xO) + 2048 + (jj >> 1) * 128);
                SCHED_FENCE(jj);
            }
            float acd[4][4];
#pragma unroll
            for (int jj = 0; jj < 4; jj++) {
#pragma unroll
                for (int mt = 0; mt < 4; mt++) {
                    if (jj == 0) { acd[mt][0] = acd[mt][1] = acd[mt][2] = acd[mt][3] = 0.f; }
                    const uint4& a = mt < 2 ? kr[4 + mt][jj] : kx[mt - 2][jj];
                    mma(acd[mt], a.x, a.y, a.z, a.w, qf[jj].x, qf[jj].y);
                }
                if (jj == 0) v_load<0, 1>(vr, va);
                if (jj == 1) v_load<1, 3>(vr, va);
                if (jj == 2) v_load<3, 5>(vr, va);
                if (jj == 3) v_load<5, 8>(vr, va);
                if (jj == 1) {
#pragma unroll
                    for (int mt = 0; mt < 4; mt++) v[mt] = acc[mt][0] + acc[mt][3];
                }
                SCHED_FENCE(4 + jj);
            }
#pragma unroll
            for (int mt = 0; mt < 4; mt++) v[4 + mt] = acd[mt][0] + acd[mt][3];
            softmax_part(c, v, m, pp, [&]() { v_load<8, 13>(vr, va); SCHED_FENCE(8); }, [&]() { v_load<13, 16>(vr, va); SCHED_FENCE(9); });
            STAMP(b2 * 16 + 6);
#pragma unroll
            for (int i = 0; i < 4; i++) { o[i][0] = o[i][1] = o[i][2] = o[i][3] = 0.f; }
            uint4 vs2[16], pw[8];
            pw[0] = lds128(pa); pw[1] = lds128(pa + 16);
            v_load<0, 2>(vs2, va + 8192);
            pw[2] = lds128(pa + 32); pw[3] = lds128(pa + 48);
            v_load<2, 4>(vs2, va + 8192);
            const unsigned lf = __float2uint_rn((__uint_as_float(pp << 16) + __uint_as_float(pp & 0xffff0000u)) * 16777216.0f);
            SCHED_FENCE(10);
            const unsigned li = __reduce_add_sync(0xffffffffu, lf);
            pv_regs<0, 2>(c, o, vr, pw);
            v_load<4, 8>(vs2, va + 8192);
            pw[4] = lds128(pa + 64); pw[5] = lds128(pa + 80);
            SCHED_FENCE(11);
            pv_regs<2, 4>(c, o, vr, pw);
            v_load<8, 13>(vs2, va + 8192);
            pw[6] = lds128(pa + 96); pw[7] = lds128(pa + 112);
            publish_ml(c, 2 + (b2 & 1), m, li);
            SCHED_FENCE(12);
            v_load<13, 16>(vs2, va + 8192);
            pv_regs<0, 2>(c, o, vs2, pw + 4);
            SCHED_FENCE(13);
            pv_regs<2, 4>(c, o, vs2, pw + 4);
            publish_part(c, o, 2 + (b2 & 1));
            SCHED_FENCE(14);
#pragma unroll
            for (int i = 0; i < 15; i++) fz ^= fv[i];
            if (c.lane == 0) { mbar_arrive(barq(sb, BAR_KXE + (b2 & 1) * 2 + (c.w >> 1))); mbar_arrive(barq(sb, BAR_EMPTY + vs)); }
            STAMP(b2 * 16 + 7);
        }
    }
    sts32(pa, fz);
}

__device__ __forceinline__ unsigned char* gptr(unsigned lo, unsigned hi) { u64 r; asm("mov.b64 %0, {%1, %2};" : "=l"(r) : "r"(lo), "r"(hi)); return (unsigned char*)r; }
template <class BAD>
__device__ __forceinline__ void poll(unsigned first, BAD bad) {
    delay(first);
    int it = 0;
    bool again;
    do { const bool more = ++it < SPIN_LIMIT; again = __any_sync(0xffffffffu, bad() && more); } while (again);
}
__device__ __forceinline__ unsigned or3x(unsigned a, unsigned b, unsigned t) { unsigned r; asm("lop3.b32 %0, %1, %2, %3, 0x7e;" : "=r"(r) : "r"(a), "r"(t), "r"(b)); return r; }
__device__ __forceinline__ unsigned or3(unsigned a, unsigned b, unsigned c) { unsigned r; asm("lop3.b32 %0, %1, %2, %3, 0xfe;" : "=r"(r) : "r"(a), "r"(b), "r"(c)); return r; }
struct Rec4 { uint4 a0, a1, a2, a3, m, n; };
__device__ __forceinline__ void poll4(const unsigned char* ra, const unsigned char* rm, unsigned tag, unsigned first, Rec4& x) {
    poll(first, [&]() {
        x.m = ld_rlx128(rm); x.n = ld_rlx128(rm + 16);
        x.a0 = ld_rlx128(ra); x.a1 = ld_rlx128(ra + 1024); x.a2 = ld_rlx128(ra + 2048); x.a3 = ld_rlx128(ra + 3072);
        return ((or3(or3x(x.m.y, x.m.w, tag), or3x(x.n.y, x.n.w, tag), or3x(x.a0.w, x.a1.w, tag)) | or3x(x.a2.w, x.a3.w, tag)) & 3u) != 0;
    });
}

__device__ __forceinline__ unsigned poll_x(const unsigned char* a, unsigned expect, unsigned first, u64 (&r)[5], uint32_t dst, int ln, int bar, float& s1, float& s2) {
    poll(first, [&]() {
#pragma unroll
        for (int v = 0; v < 5; v++) r[v] = ld_rlx64(a + voff(v));
        return (or3(or3x((unsigned)r[0], (unsigned)r[1], expect), or3x((unsigned)r[2], (unsigned)r[3], expect), (unsigned)r[4] ^ expect) & 1023u) != 0;
    });
    const unsigned w0 = pack_bf16(from_fix(r[0]), from_fix(r[1])), w1 = pack_bf16(from_fix(r[2]), from_fix(r[3])), w2 = pack_bf16(from_fix(r[4]), 0.f);
    sts32(dst + ln * 4, w0);
    sts32(dst + 128 + ln * 4, w1);
    sts16(dst + 256 + ln * 2, w2);
    nb_arrive(bar);
    const unsigned fence = clk();
    const float x0 = __uint_as_float(w0 << 16), x1 = __uint_as_float(w0 & 0xffff0000u), x2 = __uint_as_float(w1 << 16),
                x3 = __uint_as_float(w1 & 0xffff0000u), x4 = __uint_as_float(w2 << 16);
    s1 = ((x0 + x1) + (x2 + x3)) + x4;
    s2 = fmaf(x4, x4, fmaf(x0, x0, x1 * x1) + fmaf(x2, x2, x3 * x3));
#pragma unroll
    for (int o = 16; o; o >>= 1) { s1 += __shfl_xor_sync(0xffffffffu, s1, o); s2 += __shfl_xor_sync(0xffffffffu, s2, o); }
    return fence;
}
__device__ __forceinline__ uint32_t xoff(int v, int l) { return v < 4 ? (v >> 1) * 128 + l * 4 + (v & 1) * 2 : 256 + l * 2; }
__device__ __forceinline__ constexpr int krow(int s, int e) { return s < 8 ? 64 * (s >> 2) + 16 * ((s >> 1) & 1) + 2 * (s & 1) + e : 128 + 4 * (s & 1) + 2 * e; }
__device__ __forceinline__ constexpr int kstep_t(int s) { return s < 8 ? 4 : 8; }
__device__ __forceinline__ constexpr int kpair(int s) { return s < 8 ? 32 : 1; }

#undef PW
#define PW (6 + cw)
__device__ __forceinline__ void role_chain(const Params& p, uint32_t sb, int cw) {
    const int lane = threadIdx.x & 31, cta = blockIdx.x, h = cta >> 2, j = cta & 3;
    int layer = cw >> 1;
    const bool mlp = h < NGRP;
    unsigned char* const S = xbase();
    unsigned char* const grp = S + h * 65536;
    const int cv = (lane & 7) < 5 ? (lane & 7) : 0;
    unsigned char* const cadr = S + AR_OFF + j * 65536 + (h >> 3) * 1024 + (h & 7) * 8 + voff(cv) + (lane >> 3) * 4096;
    const int ccol = 160 * j + 32 * cv + h;
    const float b2v = bf16_val(ldg16(p.b2 + ccol));
    unsigned resA = 0, resB = 0;
    if (!layer) {
        const __nv_bfloat16* xp = p.x + cw * DM + ccol;
        resA = ldg16(xp) | (ldg16(xp + 2 * DM) << 16); resB = ldg16(xp + 4 * DM) | (ldg16(xp + 6 * DM) << 16);
    }
    unsigned b1p = 0;
    if (mlp) b1p = ldg32(p.b1 + 64 * h + 2 * lane);
    if (cw == 1 && h < 20) {
        unsigned char* a = S + AR_OFF + j * 65536 + (h & 3) * 1024 + voff(h >> 2) + lane * 16;
        st_rlx128(a, make_uint4(0u, 0u, 0u, 0u)); st_rlx128(a + 4096, make_uint4(0u, 0u, 0u, 0u));
        asm volatile("fence.acq_rel.gpu;" ::: "memory");
        __syncwarp();
        if (lane < 2) st_rlx128(S + FLAG_OFF + j * 1024 + h * 32 + lane * 16, make_uint4(1u, 1u, 1u, 1u));
    }
    if (cw == 2) {
        unsigned char* const flag = S + FLAG_OFF + j * 1024;
        if (lane < 24) st_rlx64(grp + (lane < 16 ? M_OFF + (lane >> 3) * 16384 : QS_OFF) + ((lane >> 2) & 1) * 4096 + (lane & 3) * 32 + j * 8, 0u, 0u);
        sts128f(sb + OFF_PREV + lane * 16, 0.f, 0.f, 0.f, 0.f);
        __syncwarp();
        mbar_wait(barq(sb, BAR_Q1), 0);
        unsigned best0 = ~0u, best1 = ~0u;
#pragma unroll 1
        for (int i = 0; i < 24; i++) {
            const unsigned t0 = clk();
            unsigned v, t1;
            asm volatile("{\n.reg .pred p;\nsetp.eq.u32 p, %2, 0;\nmov.u32 %0, 0;\n@p atom.relaxed.gpu.global.exch.b32 %0, [%1], 1;\n}"
                         : "=r"(v) : "l"(grp + QS_OFF + 64 + j * 8 + (i & 1) * 4096), "r"(lane) : "memory");
            asm volatile("and.b32 %0, %1, 0x80000000;" : "=r"(t1) : "r"(v) : "memory");
            t1 += clk();
            const unsigned dt = __shfl_sync(0xffffffffu, t1 - t0, 0);
            if (i & 1) best1 = min(best1, dt); else best0 = min(best0, dt);
            if (i >= 3 && min(best0, best1) < 390u && max(best0, best1) > min(best0, best1) + 90u) break;
        }
        const unsigned nb = best1 < best0;
        sts32(sb + OFF_NEAR, nb);
        STAMP(133);
        int it = 0;
        if (mlp) {
            mbar_wait(barq(sb, BAR_WDONE + 1), 0);
            const unsigned char* ru = grp + U_OFF + nb * 4096 + (lane >> 3) * 128 + (lane & 7) * 8;
            uint2 u0, u1, u2, u3;
            while (true) {
                u0 = ld_rlx64v(ru); u1 = ld_rlx64v(ru + 512); u2 = ld_rlx64v(ru + 1024); u3 = ld_rlx64v(ru + 1536);
                if (__all_sync(0xffffffffu, (((u0.y ^ 2u) | (u1.y ^ 2u) | (u2.y ^ 2u) | (u3.y ^ 2u)) & 3u) == 0)) break;
                if (++it > SPIN_LIMIT) bail();
            }
            sts64f(sb + OFF_CS1 + lane * 8, (__uint_as_float(u0.x) + __uint_as_float(u1.x)) + (__uint_as_float(u2.x) + __uint_as_float(u3.x)),
                   (__uint_as_float(u0.y) + __uint_as_float(u1.y)) + (__uint_as_float(u2.y) + __uint_as_float(u3.y)));
        }
        STAMP(134);
        if (lane < 2) st_rlx64(grp + M_OFF + j * 8 + lane * 4096, 0u, 2u);
        while (true) {
            unsigned f0;
            asm volatile("ld.acquire.gpu.global.u32 %0, [%1];" : "=r"(f0) : "l"(flag + (lane < 20 ? lane : 0) * 32) : "memory");
            const uint2 f1 = ld_rlx64v(grp + M_OFF + nb * 4096 + (lane & 3) * 8);
            if (__all_sync(0xffffffffu, f0 == 1u && (f1.y & 3u) != 0)) break;
            if (++it > SPIN_LIMIT) bail();
        }
        __syncwarp();
        if (lane == 0) mbar_arrive(barq(sb, BAR_NEAR));
    }
    mbar_wait(barq(sb, BAR_NEAR), 0);
    constexpr unsigned PMASK = (1u << 13) | (1u << 16) | (1u << 17) | (1u << 19);
    const unsigned nb = __shfl_sync(0xffffffffu, lds32(sb + OFF_NEAR), 0);
    const unsigned shi = (unsigned)((size_t)S >> 32), slo = (unsigned)(size_t)S;
    const unsigned ngr = nb << 12;
    const unsigned nar = ((nb ^ __popc(((AR_OFF + j * 65536) ^ (h * 65536)) & PMASK)) & 1) << 12;
    const unsigned arb = slo + AR_OFF + j * 65536;
    const unsigned clo = (unsigned)(size_t)cadr;
    STAMP(135);
#define GP(lo) gptr(lo, shi)
#define FRESH_LANE() int ln = lane; asm volatile("" : "+r"(ln))
#define F(x) __uint_as_float(x)
#define U(x) __uint2float_rn(__float_as_uint(x))

#pragma unroll 1
    for (int b = layer ? 0 : cw; b < NB - (cw >> 1); b += 2 - layer) {
        const int slot = layer * 2 + (b & 1), use = b >> 1;
        const unsigned tag = (use + 1) & 3, cbase = (use & 1) * 512;
        const unsigned gb = slo + h * 65536 + (b & 1) * 16384;
        {
            FRESH_LANE();
            const unsigned l16 = (ln >> 2) * 128 + (ln & 3) * 16;
            unsigned char* const wa = GP(gb + j * 1024 + layer * 64 + l16 + ngr);
            unsigned char* const wb = GP(gb + j * 1024 + layer * 64 + l16 + (ngr ^ 4096));
            unsigned char* const wm = GP(gb + M_OFF + layer * 32 + j * 8 + ln * 4096);
            const unsigned char* const ra = GP(gb + ngr + layer * 64 + l16);
            const unsigned char* const rm = GP(gb + ngr + M_OFF + layer * 32);
            const uint32_t pa = sb + OFF_PART + slot * 2048 + ln * 16;
            mbar_wait(barq(sb, BAR_ML + slot), use & 1);
            const float4 ml0 = lds128f(sb + OFF_ML + slot * 32), ml1 = lds128f(sb + OFF_ML + slot * 32 + 16);
            const float M = fmaxf(fmaxf(ml0.x, ml0.z), fmaxf(ml1.x, ml1.z));
            const float e0 = ex2(ml0.x - M), e1 = ex2(ml0.z - M), e2 = ex2(ml1.x - M), e3 = ex2(ml1.z - M);
            st_rlx64_if(ln < 2, wm, __float_as_uint(M), tagf(((e0 * U(ml0.y) + e1 * U(ml0.w)) + (e2 * U(ml1.y) + e3 * U(ml1.w))) * (1.0f / 16777216.0f), tag));
            nb_sync(NB_PART + slot);
            STAMPB(b * 16 + 0);
            const float4 p0 = lds128f(pa), p1 = lds128f(pa + 512), p2 = lds128f(pa + 1024), p3 = lds128f(pa + 1536);
            const uint4 pk = pkt((e0 * p0.x + e1 * p1.x) + (e2 * p2.x + e3 * p3.x), (e0 * p0.y + e1 * p1.y) + (e2 * p2.y + e3 * p3.y),
                                 (e0 * p0.z + e1 * p1.z) + (e2 * p2.z + e3 * p3.z), (e0 * p0.w + e1 * p1.w) + (e2 * p2.w + e3 * p3.w), tag);
            st_rlx128(wa, pk);
            st_rlx128(wb, pk);
            Rec4 r;
            poll(0, [&]() { r.m = ld_rlx128(rm); r.n = ld_rlx128(rm + 16); return ((or3x(r.m.y, r.m.w, tag) | or3x(r.n.y, r.n.w, tag)) & 3u) != 0; });
            r.a0 = ld_rlx128(ra); r.a1 = ld_rlx128(ra + 1024); r.a2 = ld_rlx128(ra + 2048); r.a3 = ld_rlx128(ra + 3072);
            if ((ln & 7) < 5 && ln < 16) {
                const unsigned res = layer ? lds16(sb + OFF_X2 + (b & 1) * 320 + xoff(ln & 7, h)) : (((use & 2) ? resB : resA) >> ((use & 1) * 16)) & 0xffffu;
                red64(GP(clo + boff(slot)), to_fix(bf16_val(res)) + cbase - lds64u(sb + OFF_PREV + slot * 64 + (ln & 7) * 8));
            }
            const float Mg = fmaxf(fmaxf(F(r.m.x), F(r.m.z)), fmaxf(F(r.n.x), F(r.n.z)));
            float f0 = ex2(F(r.m.x) - Mg), f1 = ex2(F(r.m.z) - Mg), f2 = ex2(F(r.n.x) - Mg), f3 = ex2(F(r.n.z) - Mg);
            const float inv = rcp(((f0 * F(r.m.y) + f1 * F(r.m.w)) + (f2 * F(r.n.y) + f3 * F(r.n.w))) * (1.0f / FIX_SCALE));
            f0 *= inv; f1 *= inv; f2 *= inv; f3 *= inv;
            asm volatile("" : "+f"(f0), "+f"(f1), "+f"(f2), "+f"(f3));
            if (__any_sync(0xffffffffu, ((or3x(r.a0.w, r.a1.w, tag) | or3x(r.a2.w, r.a3.w, tag)) & 3u) != 0))
                poll(0, [&]() {
                    r.a0 = ld_rlx128(ra); r.a1 = ld_rlx128(ra + 1024); r.a2 = ld_rlx128(ra + 2048); r.a3 = ld_rlx128(ra + 3072);
                    return ((or3x(r.a0.w, r.a1.w, tag) | or3x(r.a2.w, r.a3.w, tag)) & 3u) != 0;
                });
            STAMP(b * 16 + 1);
            const float gx = (f0 * F(r.a0.x) + f1 * F(r.a1.x)) + (f2 * F(r.a2.x) + f3 * F(r.a3.x));
            const float gy = (f0 * F(r.a0.y) + f1 * F(r.a1.y)) + (f2 * F(r.a2.y) + f3 * F(r.a3.y));
            const float gz = (f0 * F(r.a0.z) + f1 * F(r.a1.z)) + (f2 * F(r.a2.z) + f3 * F(r.a3.z));
            const float gw = (f0 * F(r.a0.w) + f1 * F(r.a1.w)) + (f2 * F(r.a2.w) + f3 * F(r.a3.w));
            sts32(sb + OFF_O + cw * 256 + ln * 4, pack_bf16(gx, gy));
            sts32(sb + OFF_O + cw * 256 + 128 + ln * 4, pack_bf16(gz, gw));
            nb_arrive(NB_O + cw);
        }
        STAMP(b * 16 + 2);
        {
            FRESH_LANE();
            const unsigned char* const ra = GP(arb + nar + boff(slot) + (ln >> 3) * 1024 + (ln & 7) * 8);
            unsigned char* const wm = GP(gb + M_OFF + 64 + layer * 32 + j * 8 + ln * 4096);
            u64 r[5];
            float s1, s2;
            delay(DELAY_AR1);
            const unsigned fence = poll_x(ra, cbase + CNT1, 0, r, sb + OFF_X1 + cw * 320, ln, NB_X1 + cw, s1, s2);
            STAMP(b * 16 + 3);
            if (ln < 2 && mlp) st_rlx64(wm, __float_as_uint(s1), tagf(s2, tag));
            if ((ln & 7) < 5 && ln < 16)
                red64(GP(clo + 256 + boff(slot)), to_fix(bf16_val(lds16(sb + OFF_X1 + cw * 320 + xoff(ln & 7, h))) + b2v) + cbase
                                                      - lds64u(sb + OFF_PREV + (4 + slot) * 64 + (ln & 7) * 8));
            if (ln == h) {
#pragma unroll
                for (int v = 0; v < 5; v++) sts64u(sb + OFF_PREV + slot * 64 + v * 8, r[v]);
                sts32(sb + OFF_PREV + slot * 64 + 56, fence);
            }
        }
        if (mlp) {
            FRESH_LANE();
            const unsigned char* const ru = GP(gb + ngr + U_OFF + layer * 64 + (ln >> 3) * 128 + (ln & 7) * 8);
            const unsigned char* const rm = GP(gb + ngr + M_OFF + 64 + layer * 32);
            const float2 cs1 = lds64f(sb + OFF_CS1 + ln * 8);
            struct { uint2 u0, u1, u2, u3; uint4 m, n; } r;
            delay(DELAY_U);
            poll(0, [&]() {
                r.m = ld_rlx128(rm); r.n = ld_rlx128(rm + 16);
                r.u0 = ld_rlx64v(ru); r.u1 = ld_rlx64v(ru + 512); r.u2 = ld_rlx64v(ru + 1024); r.u3 = ld_rlx64v(ru + 1536);
                return ((or3(or3x(r.m.y, r.m.w, tag), or3x(r.n.y, r.n.w, tag), or3x(r.u0.y, r.u1.y, tag)) | or3x(r.u2.y, r.u3.y, tag)) & 3u) != 0;
            });
            STAMP(b * 16 + 4);
            const float mu = ((F(r.m.x) + F(r.m.z)) + (F(r.n.x) + F(r.n.z))) * (1.0f / DM);
            const float var = fmaxf(((F(r.m.y) + F(r.m.w)) + (F(r.n.y) + F(r.n.w))) * (1.0f / DM) - mu * mu, 0.f);
            const float rs = rsq(fmaf(var + 1e-5f, 1e-5f, var));
            const float x = (((F(r.u0.x) + F(r.u1.x)) + (F(r.u2.x) + F(r.u3.x))) - mu * cs1.x) * rs + F(b1p << 16);
            const float y = (((F(r.u0.y) + F(r.u1.y)) + (F(r.u2.y) + F(r.u3.y))) - mu * cs1.y) * rs + F(b1p & 0xffff0000u);
            constexpr float C0 = -2.0f * 0.7978845608028654f * 1.4426950408889634f;
            sts32(sb + OFF_H + cw * 128 + ln * 4, pack_bf16((x * FIX_SCALE) * rcp(1.0f + ex2(x * fmaf(x * x, 0.044715f * C0, C0))),
                                                           (y * FIX_SCALE) * rcp(1.0f + ex2(y * fmaf(y * y, 0.044715f * C0, C0)))));
            nb_arrive(NB_H + cw);
        }
        STAMP(b * 16 + 5);
        if (layer) {
            FRESH_LANE();
            if (b == NB - 1 && ln == 0) mbar_arrive(barq(sb, BAR_DONE));
            if (b == NB - 1 && h >= 5) { STAMP(b * 16 + 6); break; }
            if (h < 5) {
                const unsigned char* const a = GP(arb + nar + 256 + boff(slot) + voff(h) + (ln >> 3) * 1024 + (ln & 7) * 8);
                __nv_bfloat16* const o = p.out + 160 * j + 32 * h + ln;
                u64 r;
                poll(DELAY_AR2, [&]() { r = ld_rlx64(a); return (((unsigned)r ^ (cbase + CNT2)) & 1023u) != 0; });
                const unsigned ob = bf16_bits(from_fix(r));
                if (b == NB - 1) { o[(NB - 1) * DM] = __ushort_as_bfloat16((unsigned short)ob); STAMP(b * 16 + 6); break; }
                sts16(sb + OFF_Q + b * QSLOT + ln * 2, ob);
                if (b == NB - 2) {
#pragma unroll 1
                    for (int r = 0; r < NB - 1; r++) o[r * DM] = __ushort_as_bfloat16((unsigned short)lds16(sb + OFF_Q + r * QSLOT + ln * 2));
                }
            } else delay(DELAY_AR2 + 600);
            const unsigned char* const a = GP(clo - (ln >> 3) * 4096 + nar + 256 + boff(slot));
            u64 r;
            int it = 0;
            while (true) {
                r = ld_rlx64(a);
                if (__all_sync(0xffffffffu, (((unsigned)r ^ (cbase + CNT2)) & 1023u) == 0)) break;
                if (++it > SPIN_LIMIT) bail();
            }
            if (ln < 5) sts64u(sb + OFF_PREV + (4 + slot) * 64 + ln * 8, r);
            __syncwarp();
            if (b == NB - 3 && ln == 0) mbar_arrive(barq(sb, BAR_L25));
            STAMP(b * 16 + 6);
        } else {
            const unsigned qb = slo + h * 65536;
            {
                FRESH_LANE();
                const unsigned char* const ra = GP(arb + nar + 256 + boff(slot) + (ln >> 3) * 1024 + (ln & 7) * 8);
                unsigned char* const wm = GP(qb + QS_OFF + cw * 32 + j * 8 + ln * 4096);
                u64 r[5];
                float s1, s2;
                delay(mlp ? DELAY_AR2 : DELAY_AR2 + 600);
                const unsigned fence = poll_x(ra, cbase + CNT2, 0, r, sb + OFF_X2 + cw * 320, ln, NB_X2 + cw, s1, s2);
                STAMP(b * 16 + 6);
                if (ln < 2) st_rlx64(wm, __float_as_uint(s1), tagf(s2, tag));
                if (ln == h) {
#pragma unroll
                    for (int v = 0; v < 5; v++) sts64u(sb + OFF_PREV + (4 + slot) * 64 + v * 8, r[v]);
                    sts32(sb + OFF_PREV + (4 + slot) * 64 + 56, fence);
                }
            }
            FRESH_LANE();
            const float4 cs = lds128f(sb + OFF_CSQ + ln * 16);
            Rec4 r;
            delay(DELAY_Q);
            poll4(GP(qb + Q_OFF + (ngr ^ 4096) + cw * 64 + (ln >> 2) * 128 + (ln & 3) * 16), GP(qb + QS_OFF + ngr + cw * 32), tag, 0, r);
            STAMP(b * 16 + 7);
            const float mu = ((F(r.m.x) + F(r.m.z)) + (F(r.n.x) + F(r.n.z))) * (1.0f / DM);
            const float var = fmaxf(((F(r.m.y) + F(r.m.w)) + (F(r.n.y) + F(r.n.w))) * (1.0f / DM) - mu * mu, 0.f);
            store_q(sb, 8 + cw, ln, pksum(r.a0, r.a1, r.a2, r.a3), cs, mu, rsq(var + 1e-5f));
            if (b == NB - 1) nb_arrive(NB_QLAST);
            else { __syncwarp(); if (ln == 0) mbar_arrive(barq(sb, BAR_Q2 + cw)); }
            STAMP(b * 16 + 8);
            if (b == NB - 2) {
                mbar_wait(barq(sb, BAR_L25), 0);
                layer = 1;
            }
        }
    }
    if (cw) {
        if (cw == 1 && h < 20 && lane < 2) st_rlx128(S + FLAG_OFF + j * 1024 + h * 32 + lane * 16, make_uint4(0u, 0u, 0u, 0u));
        if (lane == 0) mbar_arrive(barq(sb, BAR_DONE));
    }
#undef GP
#undef F
#undef U
}

template <int NS>
__device__ __forceinline__ void load_wide(unsigned (&wf)[5][NS][4], uint32_t st, int w, int g, int t) {
    const uint32_t base = st + 8 * t * 320;
#pragma unroll
    for (int s = 0; s < NS; s++)
#pragma unroll
        for (int hf = 0; hf < 2; hf++)
#pragma unroll
            for (int e = 0; e < 2; e++) {
                const uint32_t r = base + (16 * NS * hf + 32 * (s >> 1) + 4 * (s & 1) + 2 * e) * 320;
                const uint2 r0 = lds64(r + 64 * w + 8 * g), r1 = lds64(r + 320 + 64 * w + 8 * g);
                const unsigned s0 = lds16(r + 256 + 16 * w + 2 * g), s1 = lds16(r + 320 + 256 + 16 * w + 2 * g);
                wf[0][s][hf + 2 * e] = lolo(r0.x, r1.x);
                wf[1][s][hf + 2 * e] = hihi(r0.x, r1.x);
                wf[2][s][hf + 2 * e] = lolo(r0.y, r1.y);
                wf[3][s][hf + 2 * e] = hihi(r0.y, r1.y);
                wf[4][s][hf + 2 * e] = lolo(s0, s1);
                asm volatile("" : "+r"(wf[4][s][hf + 2 * e]));
            }
}
template <int NS>
__device__ __forceinline__ void gemv_wide(const unsigned (&wf)[5][NS][4], uint32_t ba, unsigned lo0, unsigned lo1, unsigned hi, int t, float zero) {
    uint4 B[NS / 2];
#pragma unroll
    for (int u = 0; u < NS / 2; u++) B[u] = lds128(ba + 64 * u);
    float acc[5][4];
#pragma unroll
    for (int i = 0; i < 5; i++) { acc[i][0] = acc[i][1] = acc[i][2] = acc[i][3] = 0.f; }
#pragma unroll
    for (int s = 0; s < NS; s++)
#pragma unroll
        for (int i = 0; i < 5; i++)
            mma(acc[i], wf[i][s][0], wf[i][s][1], wf[i][s][2], wf[i][s][3], (s & 1) ? B[s >> 1].z : B[s >> 1].x, (s & 1) ? B[s >> 1].w : B[s >> 1].y);
    const float v0 = fmaf(acc[4][0], zero, acc[0][0]) + acc[0][3], v1 = acc[1][0] + acc[1][3], v2 = acc[2][0] + acc[2][3], v3 = acc[3][0] + acc[3][3];
    const u64 fa = __float2ll_rn((t & 2) ? ((t & 1) ? v3 : v2) : ((t & 1) ? v1 : v0)), fb = __float2ll_rn(acc[4][0] + acc[4][3]);
    unsigned al, bl;
    asm("lop3.b32 %0, %1, 0xfffffc00, %2, 0xea;" : "=r"(al) : "r"((unsigned)fa), "r"(1u));
    asm("lop3.b32 %0, %1, 0xfffffc00, %2, 0xea;" : "=r"(bl) : "r"((unsigned)fb), "r"(1u));
    asm volatile("{\n.reg .pred p;\n.reg .b64 a, b;\nsetp.lt.u32 p, %6, 2;\nmov.b64 a, {%1, %2};\nmov.b64 b, {%4, %5};\n"
                 "red.relaxed.gpu.global.add.u64 [%0], a;\n"
                 "red.relaxed.gpu.global.add.u64 [%0+4096], a;\n"
                 "@p red.relaxed.gpu.global.add.u64 [%3], b;\n}"
                 :: "l"(gptr(lo0, hi)), "r"(al), "r"((unsigned)(fa >> 32)), "l"(gptr(lo1, hi)), "r"(bl), "r"((unsigned)(fb >> 32)), "r"(t) : "memory");
}

#undef PW
#define PW 4
__device__ __forceinline__ void role_g1(const Params& p, uint32_t sb, int w) {
    const int lane = threadIdx.x & 31, g = lane >> 2, t = lane & 3;
    const int cta = blockIdx.x, h = cta >> 2, j = cta & 3;
    const bool mlp = h < NGRP;
    unsigned wf[5][4][4], w1f[10][4];
    {
        mbar_wait(barq(sb, BAR_W + WP_W1), 0); mbar_wait(barq(sb, BAR_W + WP_W1 + 1), 0);
        const uint32_t base1 = sb + ST_W1 + 32 * w + 4 * g;
#pragma unroll
        for (int s = 0; s < 10; s++)
#pragma unroll
            for (int e = 0; e < 2; e++) {
                const uint32_t r = base1 + (krow(s, e) + kstep_t(s) * t) * 128;
                const unsigned r0 = lds32(r), r1 = lds32(r + kpair(s) * 128);
                w1f[s][2 * e] = lolo(r0, r1);
                w1f[s][2 * e + 1] = hihi(r0, r1);
            }
        float a[4] = {0.f, 0.f, 0.f, 0.f};
#pragma unroll
        for (int s = 0; s < 10; s++) mma(a, w1f[s][0], w1f[s][1], w1f[s][2], w1f[s][3], 0x3f803f80u, 0x3f803f80u);
        if (mlp) {
            unsigned char* ua = xbase() + h * 65536 + U_OFF + j * 512 + w * 128 + g * 8 + (t >> 1) * 64 + (t & 1) * 4096;
            st_rlx64(ua, __float_as_uint(a[0]), tagf(a[2], 2u));
            st_rlx64(ua + 16384, __float_as_uint(a[0]), tagf(a[2], 2u));
        }
#pragma unroll 1
        for (int m = WP_WO; m < WP_WO + 4; m++) mbar_wait(barq(sb, BAR_W + m), 0);
        load_wide<4>(wf, sb + ST_WO, w, g, t);
        __syncwarp();
        if (lane == 0) mbar_arrive(barq(sb, BAR_WDONE + 1));
    }
    STAMP(135);
    const unsigned shi = (unsigned)((size_t)xbase() >> 32), slo = (unsigned)(size_t)xbase();
    const unsigned ra0 = slo + AR_OFF + j * 65536 + (lane >> 3) * 1024 + (lane & 7) * 8 + voff(w);
    const unsigned gt = g * 8 + t * 4096;
    const unsigned ra1 = slo + AR_OFF + j * 65536 + w * 1024 + voff(4), ua = slo + h * 65536 + U_OFF + j * 512 + 128 * w;
    const uint32_t ob = sb + OFF_O + (g & 1) * 128 + t * 16, xb = sb + OFF_X1 + t * 16;
#pragma unroll 1
    for (int n = 0; n < 16; n++) {
        int layer, b; item_of(n, layer, b);
        const int slot = layer * 2 + (b & 1), cw = n == 15 ? 0 : layer ? 2 : (b & 1);
        const unsigned tag = ((b >> 1) + 1) & 3;
        nb_sync(NB_O + cw);
        STAMPB(n * 8 + 0);
        gemv_wide<4>(wf, ob + cw * 256, ra0 + boff(slot), gt + (ra1 + boff(slot)), shi, t, p.zero);
        STAMP(n * 8 + 1);
        nb_sync(NB_X1 + cw);
        STAMPB(n * 8 + 2);
        if (mlp) {
            uint4 B[5];
#pragma unroll
            for (int u = 0; u < 5; u++) B[u] = lds128(xb + cw * 320 + 64 * u);
            float a[4][4];
#pragma unroll
            for (int i = 0; i < 4; i++) { a[i][0] = a[i][1] = a[i][2] = a[i][3] = 0.f; }
#pragma unroll
            for (int s = 0; s < 10; s++)
                mma(a[s & 3], w1f[s][0], w1f[s][1], w1f[s][2], w1f[s][3], (s & 1) ? B[s >> 1].z : B[s >> 1].x, (s & 1) ? B[s >> 1].w : B[s >> 1].y);
            st_rlx64_if(t < 2, gptr(gt + (ua + (b & 1) * 16384 + layer * 64), shi), __float_as_uint((a[2][0] + a[3][0]) + (a[0][0] + a[1][0])), tagf((a[2][2] + a[3][2]) + (a[0][2] + a[1][2]), tag));
        }
        STAMP(n * 8 + 3);
    }
    if (lane == 0) mbar_arrive(barq(sb, BAR_DONE));
}

#undef PW
#define PW 5
__device__ __forceinline__ void role_g2(const Params& p, uint32_t sb, int w) {
    const int lane = threadIdx.x & 31, g = lane >> 2, t = lane & 3;
    const int cta = blockIdx.x, h = cta >> 2, j = cta & 3;
    const bool mlp = h < NGRP;
    unsigned wf[2][10][4], w2f[5][2][4];
    {
        uint4 X[5];
#pragma unroll
        for (int u = 0; u < 4; u++) {
            const __nv_bfloat16* xp = p.x + g * DM + 160 * j + krow(2 * u, 0) + 4 * t;
            const uint2 lo = ldg64(xp), hi = ldg64(xp + 32);
            X[u] = make_uint4(lolo(lo.x, hi.x), hihi(lo.x, hi.x), lolo(lo.y, hi.y), hihi(lo.y, hi.y));
        }
        X[4] = __ldg((const uint4*)(p.x + g * DM + 160 * j + 128 + 8 * t));
#pragma unroll 1
        for (int m = WP_WQ; m < WP_WQ + 4; m++) mbar_wait(barq(sb, BAR_W + m), 0);
        STAMP(130);
        const uint32_t base = sb + ST_WQ + 64 * w + 8 * g;
#pragma unroll
        for (int s = 0; s < 10; s++)
#pragma unroll
            for (int e = 0; e < 2; e++) {
                const uint32_t r = base + (krow(s, e) + kstep_t(s) * t) * 256;
                const uint2 r0 = lds64(r), r1 = lds64(r + kpair(s) * 256);
                wf[0][s][2 * e] = lolo(r0.x, r1.x);
                wf[0][s][2 * e + 1] = hihi(r0.x, r1.x);
                wf[1][s][2 * e] = lolo(r0.y, r1.y);
                wf[1][s][2 * e + 1] = hihi(r0.y, r1.y);
            }
        {
            float a[4] = {0.f, 0.f, 0.f, 0.f}, c[4] = {0.f, 0.f, 0.f, 0.f}, sa[4] = {0.f, 0.f, 0.f, 0.f}, sc[4] = {0.f, 0.f, 0.f, 0.f};
#pragma unroll
            for (int s = 0; s < 10; s++) {
                const unsigned b0 = (s & 1) ? X[s >> 1].z : X[s >> 1].x, b1 = (s & 1) ? X[s >> 1].w : X[s >> 1].y;
                mma(a, wf[0][s][0], wf[0][s][1], wf[0][s][2], wf[0][s][3], b0, b1);
                mma(c, wf[1][s][0], wf[1][s][1], wf[1][s][2], wf[1][s][3], b0, b1);
                mma(sa, wf[0][s][0], wf[0][s][1], wf[0][s][2], wf[0][s][3], 0x3f803f80u, 0x3f803f80u);
                mma(sc, wf[1][s][0], wf[1][s][1], wf[1][s][2], wf[1][s][3], 0x3f803f80u, 0x3f803f80u);
            }
            unsigned char* qm = xbase() + h * 65536 + j * 1024 + (8 * w + g) * 16;
            st_rlx128(qm + (t & 1) * 16384 + (t >> 1) * 4096, pkt(a[0], a[2], c[0], c[2], 2u));
            st_rlx128(qm + (t & 1) * 16384 + (t >> 1) * 4096 + 512, pkt(a[1], a[3], c[1], c[3], 2u));
            st_rlx128(qm + Q_OFF + (t >> 1) * 512 + (t & 1) * 4096, pkt(sa[0], sa[2], sc[0], sc[2], 2u));
        }
        mbar_wait(barq(sb, BAR_W + WP_W2), 0); mbar_wait(barq(sb, BAR_W + WP_W2 + 1), 0);
        load_wide<2>(w2f, sb + ST_W2, w, g, t);
        __syncwarp();
        if (lane == 0) mbar_arrive(barq(sb, BAR_WDONE));
        STAMP(131);
    }
    const unsigned shi = (unsigned)((size_t)xbase() >> 32), slo = (unsigned)(size_t)xbase();
    const unsigned ra0 = slo + AR_OFF + j * 65536 + (lane >> 3) * 1024 + (lane & 7) * 8 + voff(w) + 256;
    const unsigned ra1 = slo + AR_OFF + j * 65536 + w * 1024 + g * 8 + voff(4) + t * 4096 + 256;
    const unsigned qa = slo + h * 65536 + Q_OFF + j * 1024 + (2 * w + (g >> 2)) * 128 + (g & 3) * 16 + t * 4096;
    const uint32_t hb = sb + OFF_H + (g & 1) * 64 + t * 16, xb = sb + OFF_X2 + t * 16;
    STAMP(135);
#pragma unroll 1
    for (int n = 0; n < 16; n++) {
        int layer, b; item_of(n, layer, b);
        const int slot = layer * 2 + (b & 1), cw = n == 15 ? 0 : layer ? 2 : (b & 1);
        if (mlp) {
            nb_sync(NB_H + cw);
            STAMPB(n * 8 + 0);
            gemv_wide<2>(w2f, hb + cw * 128, ra0 + boff(slot), ra1 + boff(slot), shi, t, p.zero);
            STAMP(n * 8 + 1);
        }
        if (layer == 0) {
            nb_sync(NB_X2 + cw);
            STAMPB(n * 8 + 2);
            float a0[4] = {0.f, 0.f, 0.f, 0.f}, a1[4] = {0.f, 0.f, 0.f, 0.f}, c0[4] = {0.f, 0.f, 0.f, 0.f}, c1[4] = {0.f, 0.f, 0.f, 0.f};
            uint4 B[5];
#pragma unroll
            for (int u = 0; u < 5; u++) B[u] = lds128(xb + cw * 320 + 64 * u);
#pragma unroll
            for (int u = 0; u < 5; u++) {
                mma(a0, wf[0][2 * u][0], wf[0][2 * u][1], wf[0][2 * u][2], wf[0][2 * u][3], B[u].x, B[u].y);
                mma(c0, wf[1][2 * u][0], wf[1][2 * u][1], wf[1][2 * u][2], wf[1][2 * u][3], B[u].x, B[u].y);
                mma(a1, wf[0][2 * u + 1][0], wf[0][2 * u + 1][1], wf[0][2 * u + 1][2], wf[0][2 * u + 1][3], B[u].z, B[u].w);
                mma(c1, wf[1][2 * u + 1][0], wf[1][2 * u + 1][1], wf[1][2 * u + 1][2], wf[1][2 * u + 1][3], B[u].z, B[u].w);
            }
            st_rlx128_if(t < 2, gptr(qa + cw * 64, shi), pkt(a0[0] + a1[0], a0[2] + a1[2], c0[0] + c1[0], c0[2] + c1[2], ((b >> 1) + 1) & 3));
            STAMP(n * 8 + 3);
        }
    }
    if (lane == 0) mbar_arrive(barq(sb, BAR_DONE));
}

#define REG_ATT 128
#define REG_G1 160
#define REG_G2 160
#define REG_AUX 64
template <int N> __device__ __forceinline__ void set_regs() {
    if (N > 128) asm volatile("setmaxnreg.inc.sync.aligned.u32 %0;" :: "n"(N));
    if (N < 128) asm volatile("setmaxnreg.dec.sync.aligned.u32 %0;" :: "n"(N));
}

#define PROF_DUMP() do {} while (0)

__global__ void __launch_bounds__(512, 1) fused_kernel(const __grid_constant__ Params p) {
    extern __shared__ __align__(128) unsigned char smem[];
    const uint32_t sb = (uint32_t)__cvta_generic_to_shared(smem);
    const int cta = blockIdx.x;
    const unsigned t0 = gtime();
    const size_t kvoff = ((size_t)(cta >> 2) * SK + (SK - WIN) + (cta & 3) * 256) * 256;
    const char* kbase = (const char*)p.k + kvoff;
    const int warp = __shfl_sync(0xffffffffu, threadIdx.x >> 5, 0), lane = threadIdx.x & 31;
    if (warp < NFIRST) {
        if (elect_one()) {
            const uint32_t bar = barq(sb, BAR_FULL + warp);
            mbar_init(bar, 1);
            asm volatile("fence.mbarrier_init.release.cluster;" ::: "memory");
            mbar_expect_tx(bar, TILE / 2);
            asm volatile("cp.async.bulk.shared::cluster.global.mbarrier::complete_tx::bytes [%0], [%1], %2, [%3];"
                         :: "r"(sb + warp * (TILE / 2)), "l"(kbase + warp * (TILE / 2)), "r"(TILE / 2), "r"(bar) : "memory");
        }
#undef PW
#define PW 9
        STAMP(0);
    }
    asm volatile("" ::: "memory");
    if (warp >= 4 && warp < 8) {
        if (elect_one()) {
            const uint32_t bar = barq(sb, BAR_W + warp - 4);
            mbar_init(bar, 1);
            asm volatile("fence.mbarrier_init.release.cluster;" ::: "memory");
            mbar_expect_tx(bar, 10240);
            tma2d(sb + ST_WQ + (warp - 4) * 10240, &p.tq, (cta >> 2) * 128, 160 * (cta & 3) + 40 * (warp - 4), bar);
        }
    }
    asm volatile("" ::: "memory");
    if (warp >= 8) {
        if (elect_one()) {
#pragma unroll 1
            for (int bi = warp - 4; bi < NBAR; bi += 8)
                if ((bi & ~3) != BAR_W) mbar_init(barq(sb, bi), (bi == BAR_Q1 || bi >= BAR_WDONE) ? 4 : bi == BAR_DONE ? 15 : bi >= BAR_KXE ? 2 : 1);
            asm volatile("fence.mbarrier_init.release.cluster;" ::: "memory");
            if (warp >= 13) asm volatile("prefetch.tensormap [%0];" :: "l"(&p.tq + (warp - 12)) : "memory");
        }
    }
    __syncthreads();
    if (warp < 4) {
        set_regs<REG_ATT>();
        role_att(p, sb, kbase, warp);
        PROF_DUMP();
    } else if (warp < 8) {
        set_regs<REG_G1>();
        role_g1(p, sb, warp - 4);
        PROF_DUMP();
    } else if (warp < 12) {
        set_regs<REG_G2>();
        role_g2(p, sb, warp - 8);
        PROF_DUMP();
    } else {
        set_regs<REG_AUX>();
        if (warp == 12) role_producer(p, sb, kbase, (const char*)p.v + kvoff, t0);
        else role_chain(p, sb, warp - 13);
        PROF_DUMP();
    }
}

}

typedef CUresult (*EncodeTiledFn)(CUtensorMap*, CUtensorMapDataType, cuuint32_t, void*, const cuuint64_t*, const cuuint64_t*, const cuuint32_t*,
                                  const cuuint32_t*, CUtensorMapInterleave, CUtensorMapSwizzle, CUtensorMapL2promotion, CUtensorMapFloatOOBfill);

static void make_map(EncodeTiledFn enc, CUtensorMap* tm, void* ptr, int cols, int rows, int bcols, int brows, int promo = 0) {
    cuuint64_t gd[2] = {(cuuint64_t)cols, (cuuint64_t)rows}, gs[1] = {(cuuint64_t)cols * 2};
    cuuint32_t bd[2] = {(cuuint32_t)bcols, (cuuint32_t)brows}, es[2] = {1, 1};
    enc(tm, CU_TENSOR_MAP_DATA_TYPE_BFLOAT16, 2, ptr, gd, gs, bd, es, CU_TENSOR_MAP_INTERLEAVE_NONE, CU_TENSOR_MAP_SWIZZLE_NONE,
        (CUtensorMapL2promotion)promo, CU_TENSOR_MAP_FLOAT_OOB_FILL_NONE);
}

extern "C" void kernel_launch(void* const* d_in, const int* in_sizes, int n_in, void* d_out, int out_size) {
    void* fn = nullptr;
    cudaDriverEntryPointQueryResult qr;
    cudaGetDriverEntryPoint("cuTensorMapEncodeTiled", &fn, cudaEnableDefault, &qr);
    Params p;
    make_map((EncodeTiledFn)fn, &p.tq, d_in[3], 4096, DM, 128, 40);
    const int promo = 0;
    make_map((EncodeTiledFn)fn, &p.to, d_in[4], DM, 4096, 160, 32, promo);
    make_map((EncodeTiledFn)fn, &p.t1, d_in[6], FF, DM, 64, 80, promo);
    make_map((EncodeTiledFn)fn, &p.t2, d_in[8], DM, FF, 160, 32, promo);
    p.x = (const __nv_bfloat16*)d_in[0];
    p.k = (const __nv_bfloat16*)d_in[1];
    p.v = (const __nv_bfloat16*)d_in[2];
    p.b1 = (const __nv_bfloat16*)d_in[7];
    p.b2 = (const __nv_bfloat16*)d_in[9];
    p.out = (__nv_bfloat16*)d_out;
    p.zero = 0.f;
    cudaFuncSetAttribute(fused_kernel, cudaFuncAttributeMaxDynamicSharedMemorySize, SMEM_BYTES);
    fused_kernel<<<NCTA, 512, SMEM_BYTES>>>(p);
}
```
